```python
import torch

def _softmax(x, axis=-1):
    return torch.softmax(x, dim=axis)
def _gelu(x):
    return torch.nn.functional.gelu(x, approximate="tanh")
def _silu(x):
    return torch.nn.functional.silu(x)
def _sigmoid(x):
    return torch.sigmoid(x)
def _layernorm(x, axis=-1, eps=1e-5):
    m = x.mean(dim=axis, keepdim=True)
    v = x.var(dim=axis, keepdim=True, unbiased=False)
    return (x - m) / torch.sqrt(v + eps)
def _scatter_add(tgt, idx, src, axis=0):
    return tgt.clone().index_add_(axis, idx, src)
def _segment_sum(src, seg, n):
    out = torch.zeros((n,) + src.shape[1:], dtype=src.dtype)
    return out.index_add_(0, seg, src)
def _pad(x, pw):
    flat = tuple(v for pair in reversed(pw) for v in pair)
    return torch.nn.functional.pad(x, flat)

kernel_name = 'gated_mix__linear_kernel_hedgehog__glu_gated_bilinear__prompt'

def setup_inputs():

    _w = (lambda a: (lambda t: t.to(torch.bfloat16) if t.is_floating_point() else t)(torch.as_tensor(a)))
    def _A_setup():
        B, S, D, H = 1, 2048, 512, 32
        Dh = D // H
        return {
            "x": _w((lambda *s: torch.randn(*s, dtype=torch.bfloat16) * 0.05)(B, S, D)),
            "wqkv": _w((lambda *s: torch.randn(*s, dtype=torch.bfloat16) * 0.8)(D, 3 * D)),
            "w_phi": _w((lambda *s: torch.randn(*s, dtype=torch.bfloat16) * 0.8)(H, Dh, Dh) * (Dh ** -0.5)),
            "wo": _w((lambda *s: torch.randn(*s, dtype=torch.bfloat16) * 0.05)(D, D)),
        }
    _A_in = _A_setup()

    def _B_setup():
        B, S, D, F = 1, 2048, 512, 1792
        return {
            "x": _w((lambda *s: torch.randn(*s, dtype=torch.bfloat16) * 0.05)(B, S, D)),
            "w_gate": _w((lambda *s: torch.randn(*s, dtype=torch.bfloat16) * 1.6)(D, F) * (D ** -0.5)),
            "w_up": _w((lambda *s: torch.randn(*s, dtype=torch.bfloat16) * 1.6)(D, F) * (D ** -0.5)),
            "w_down": _w((lambda *s: torch.randn(*s, dtype=torch.bfloat16) * 1.6)(F, D) * (F ** -0.5)),
        }
    _B_in = _B_setup()

    return {
        "A_x": _A_in["x"],
        "A_wqkv": _A_in["wqkv"],
        "A_w_phi": _A_in["w_phi"],
        "A_wo": _A_in["wo"],
        "B_x": _B_in["x"],
        "B_w_gate": _B_in["w_gate"],
        "B_w_up": _B_in["w_up"],
        "B_w_down": _B_in["w_down"],
        "gate_w": _w((lambda *s: torch.randn(*s, dtype=torch.bfloat16) * 0.05)(512) * 16.0),
    }

def reference(A_x, A_wqkv, A_w_phi, A_wo, B_x, B_w_gate, B_w_up, B_w_down, gate_w):
    def _A_ref(x, wqkv, w_phi, wo):
        B, S, D = x.shape
        H = 32; Dh = D // H
        qkv = (lambda x, *d: x.permute(*d))((x @ wqkv).reshape(B, S, 3, H, Dh), 2, 0, 3, 1, 4)
        q, k, v = qkv[0], qkv[1], qkv[2]
        pq = torch.einsum("bhsd,hdf->bhsf", q, w_phi)
        pk = torch.einsum("bhsd,hdf->bhsf", k, w_phi)
        phi_q = torch.concatenate([_softmax(pq, axis=-1), _softmax(-pq, axis=-1)], axis=-1)
        phi_k = torch.concatenate([_softmax(pk, axis=-1), _softmax(-pk, axis=-1)], axis=-1)
        kv = torch.einsum("bhsf,bhsd->bhfd", phi_k, v)
        z  = torch.einsum("bhsf->bhf", phi_k)
        num = torch.einsum("bhqf,bhfd->bhqd", phi_q, kv)
        den = torch.einsum("bhqf,bhf->bhq", phi_q, z)[..., None] + 1e-6
        o = num / den
        return (lambda x, *d: x.permute(*d))(o, 0, 2, 1, 3).reshape(B, S, D) @ wo

    def _B_ref(x, w_gate, w_up, w_down):
        g = torch.einsum("bsd,df->bsf", x, w_gate)
        u = torch.einsum("bsd,df->bsf", x, w_up)
        h = g * u
        return torch.einsum("bsf,fd->bsd", h, w_down)

    x = A_x
    g = _sigmoid((x * gate_w).sum(-1, keepdims=True))
    a = _A_ref(x, A_wqkv, A_w_phi, A_wo)
    b = _B_ref(x, B_w_gate, B_w_up, B_w_down)
    return g * a + (1 - g) * b
```

```cpp
#include <cuda_runtime.h>
#include <cuda.h>
#include <cuda_bf16.h>
#include <stdint.h>
#include <type_traits>

template <uint32_t AI, uint32_t BI> __device__ __forceinline__ void wg_ss128_t01_p(float (&d)[64], uint32_t abase, uint32_t sd) {
  asm volatile("{\n.reg .pred p;\n.reg .b32 t;\n.reg .b64 da, db;\nsetp.ne.b32 p, %67, 0;\nadd.u32 t, %64, %65;\n"
    "mov.b64 da, {t, 0x40000040};\nmov.b64 db, {%66, 0x40000040};\n"
    "wgmma.mma_async.sync.aligned.m64n128k16.f32.bf16.bf16 "
    "{%0, %1, %2, %3, %4, %5, %6, %7, %8, %9, %10, %11, %12, %13, %14, %15, %16, %17, %18, %19, %20, %21, %22, %23, %24, %25, %26, %27, %28, %29, %30, %31, %32, %33, %34, %35, %36, %37, %38, %39, %40, %41, %42, %43, %44, %45, %46, %47, %48, %49, %50, %51, %52, %53, %54, %55, %56, %57, %58, %59, %60, %61, %62, %63}, da, db, p, 1, 1, 0, 1;\n}\n"
    : "+f"(d[0]), "+f"(d[1]), "+f"(d[2]), "+f"(d[3]), "+f"(d[4]), "+f"(d[5]), "+f"(d[6]), "+f"(d[7]), "+f"(d[8]), "+f"(d[9]), "+f"(d[10]), "+f"(d[11]), "+f"(d[12]), "+f"(d[13]), "+f"(d[14]), "+f"(d[15]), "+f"(d[16]), "+f"(d[17]), "+f"(d[18]), "+f"(d[19]), "+f"(d[20]), "+f"(d[21]), "+f"(d[22]), "+f"(d[23]), "+f"(d[24]), "+f"(d[25]), "+f"(d[26]), "+f"(d[27]), "+f"(d[28]), "+f"(d[29]), "+f"(d[30]), "+f"(d[31]), "+f"(d[32]), "+f"(d[33]), "+f"(d[34]), "+f"(d[35]), "+f"(d[36]), "+f"(d[37]), "+f"(d[38]), "+f"(d[39]), "+f"(d[40]), "+f"(d[41]), "+f"(d[42]), "+f"(d[43]), "+f"(d[44]), "+f"(d[45]), "+f"(d[46]), "+f"(d[47]), "+f"(d[48]), "+f"(d[49]), "+f"(d[50]), "+f"(d[51]), "+f"(d[52]), "+f"(d[53]), "+f"(d[54]), "+f"(d[55]), "+f"(d[56]), "+f"(d[57]), "+f"(d[58]), "+f"(d[59]), "+f"(d[60]), "+f"(d[61]), "+f"(d[62]), "+f"(d[63])
    : "r"(abase), "n"(AI), "n"(BI), "r"(sd));
}
template <uint32_t AI, uint32_t BI> __device__ __forceinline__ void wg_ss256_t01(float (&d)[128], uint32_t abase) {
  asm volatile("{\n.reg .pred p;\n.reg .b32 t;\n.reg .b64 da, db;\nsetp.ne.b32 p, 1, 0;\nadd.u32 t, %128, %129;\n"
    "mov.b64 da, {t, 0x40000040};\nmov.b64 db, {%130, 0x40000040};\n"
    "wgmma.mma_async.sync.aligned.m64n256k16.f32.bf16.bf16 "
    "{%0, %1, %2, %3, %4, %5, %6, %7, %8, %9, %10, %11, %12, %13, %14, %15, %16, %17, %18, %19, %20, %21, %22, %23, %24, %25, %26, %27, %28, %29, %30, %31, %32, %33, %34, %35, %36, %37, %38, %39, %40, %41, %42, %43, %44, %45, %46, %47, %48, %49, %50, %51, %52, %53, %54, %55, %56, %57, %58, %59, %60, %61, %62, %63, %64, %65, %66, %67, %68, %69, %70, %71, %72, %73, %74, %75, %76, %77, %78, %79, %80, %81, %82, %83, %84, %85, %86, %87, %88, %89, %90, %91, %92, %93, %94, %95, %96, %97, %98, %99, %100, %101, %102, %103, %104, %105, %106, %107, %108, %109, %110, %111, %112, %113, %114, %115, %116, %117, %118, %119, %120, %121, %122, %123, %124, %125, %126, %127}, da, db, p, 1, 1, 0, 1;\n}\n"
    : "+f"(d[0]), "+f"(d[1]), "+f"(d[2]), "+f"(d[3]), "+f"(d[4]), "+f"(d[5]), "+f"(d[6]), "+f"(d[7]), "+f"(d[8]), "+f"(d[9]), "+f"(d[10]), "+f"(d[11]), "+f"(d[12]), "+f"(d[13]), "+f"(d[14]), "+f"(d[15]), "+f"(d[16]), "+f"(d[17]), "+f"(d[18]), "+f"(d[19]), "+f"(d[20]), "+f"(d[21]), "+f"(d[22]), "+f"(d[23]), "+f"(d[24]), "+f"(d[25]), "+f"(d[26]), "+f"(d[27]), "+f"(d[28]), "+f"(d[29]), "+f"(d[30]), "+f"(d[31]), "+f"(d[32]), "+f"(d[33]), "+f"(d[34]), "+f"(d[35]), "+f"(d[36]), "+f"(d[37]), "+f"(d[38]), "+f"(d[39]), "+f"(d[40]), "+f"(d[41]), "+f"(d[42]), "+f"(d[43]), "+f"(d[44]), "+f"(d[45]), "+f"(d[46]), "+f"(d[47]), "+f"(d[48]), "+f"(d[49]), "+f"(d[50]), "+f"(d[51]), "+f"(d[52]), "+f"(d[53]), "+f"(d[54]), "+f"(d[55]), "+f"(d[56]), "+f"(d[57]), "+f"(d[58]), "+f"(d[59]), "+f"(d[60]), "+f"(d[61]), "+f"(d[62]), "+f"(d[63]), "+f"(d[64]), "+f"(d[65]), "+f"(d[66]), "+f"(d[67]), "+f"(d[68]), "+f"(d[69]), "+f"(d[70]), "+f"(d[71]), "+f"(d[72]), "+f"(d[73]), "+f"(d[74]), "+f"(d[75]), "+f"(d[76]), "+f"(d[77]), "+f"(d[78]), "+f"(d[79]), "+f"(d[80]), "+f"(d[81]), "+f"(d[82]), "+f"(d[83]), "+f"(d[84]), "+f"(d[85]), "+f"(d[86]), "+f"(d[87]), "+f"(d[88]), "+f"(d[89]), "+f"(d[90]), "+f"(d[91]), "+f"(d[92]), "+f"(d[93]), "+f"(d[94]), "+f"(d[95]), "+f"(d[96]), "+f"(d[97]), "+f"(d[98]), "+f"(d[99]), "+f"(d[100]), "+f"(d[101]), "+f"(d[102]), "+f"(d[103]), "+f"(d[104]), "+f"(d[105]), "+f"(d[106]), "+f"(d[107]), "+f"(d[108]), "+f"(d[109]), "+f"(d[110]), "+f"(d[111]), "+f"(d[112]), "+f"(d[113]), "+f"(d[114]), "+f"(d[115]), "+f"(d[116]), "+f"(d[117]), "+f"(d[118]), "+f"(d[119]), "+f"(d[120]), "+f"(d[121]), "+f"(d[122]), "+f"(d[123]), "+f"(d[124]), "+f"(d[125]), "+f"(d[126]), "+f"(d[127])
    : "r"(abase), "n"(AI), "n"(BI));
}
template <uint32_t AI, uint32_t BI> __device__ __forceinline__ void wg_ss128_t01(float (&d)[64], uint32_t abase) {
  asm volatile("{\n.reg .pred p;\n.reg .b32 t;\n.reg .b64 da, db;\nsetp.ne.b32 p, 1, 0;\nadd.u32 t, %64, %65;\n"
    "mov.b64 da, {t, 0x40000040};\nmov.b64 db, {%66, 0x40000040};\n"
    "wgmma.mma_async.sync.aligned.m64n128k16.f32.bf16.bf16 "
    "{%0, %1, %2, %3, %4, %5, %6, %7, %8, %9, %10, %11, %12, %13, %14, %15, %16, %17, %18, %19, %20, %21, %22, %23, %24, %25, %26, %27, %28, %29, %30, %31, %32, %33, %34, %35, %36, %37, %38, %39, %40, %41, %42, %43, %44, %45, %46, %47, %48, %49, %50, %51, %52, %53, %54, %55, %56, %57, %58, %59, %60, %61, %62, %63}, da, db, p, 1, 1, 0, 1;\n}\n"
    : "+f"(d[0]), "+f"(d[1]), "+f"(d[2]), "+f"(d[3]), "+f"(d[4]), "+f"(d[5]), "+f"(d[6]), "+f"(d[7]), "+f"(d[8]), "+f"(d[9]), "+f"(d[10]), "+f"(d[11]), "+f"(d[12]), "+f"(d[13]), "+f"(d[14]), "+f"(d[15]), "+f"(d[16]), "+f"(d[17]), "+f"(d[18]), "+f"(d[19]), "+f"(d[20]), "+f"(d[21]), "+f"(d[22]), "+f"(d[23]), "+f"(d[24]), "+f"(d[25]), "+f"(d[26]), "+f"(d[27]), "+f"(d[28]), "+f"(d[29]), "+f"(d[30]), "+f"(d[31]), "+f"(d[32]), "+f"(d[33]), "+f"(d[34]), "+f"(d[35]), "+f"(d[36]), "+f"(d[37]), "+f"(d[38]), "+f"(d[39]), "+f"(d[40]), "+f"(d[41]), "+f"(d[42]), "+f"(d[43]), "+f"(d[44]), "+f"(d[45]), "+f"(d[46]), "+f"(d[47]), "+f"(d[48]), "+f"(d[49]), "+f"(d[50]), "+f"(d[51]), "+f"(d[52]), "+f"(d[53]), "+f"(d[54]), "+f"(d[55]), "+f"(d[56]), "+f"(d[57]), "+f"(d[58]), "+f"(d[59]), "+f"(d[60]), "+f"(d[61]), "+f"(d[62]), "+f"(d[63])
    : "r"(abase), "n"(AI), "n"(BI));
}
template <uint32_t AI, uint32_t BI> __device__ __forceinline__ void wg_ss128_t10(float (&d)[64], uint32_t abase) {
  asm volatile("{\n.reg .pred p;\n.reg .b32 t;\n.reg .b64 da, db;\nsetp.ne.b32 p, 1, 0;\nadd.u32 t, %64, %65;\n"
    "mov.b64 da, {t, 0x40000040};\nmov.b64 db, {%66, 0x40000040};\n"
    "wgmma.mma_async.sync.aligned.m64n128k16.f32.bf16.bf16 "
    "{%0, %1, %2, %3, %4, %5, %6, %7, %8, %9, %10, %11, %12, %13, %14, %15, %16, %17, %18, %19, %20, %21, %22, %23, %24, %25, %26, %27, %28, %29, %30, %31, %32, %33, %34, %35, %36, %37, %38, %39, %40, %41, %42, %43, %44, %45, %46, %47, %48, %49, %50, %51, %52, %53, %54, %55, %56, %57, %58, %59, %60, %61, %62, %63}, da, db, p, 1, 1, 1, 0;\n}\n"
    : "+f"(d[0]), "+f"(d[1]), "+f"(d[2]), "+f"(d[3]), "+f"(d[4]), "+f"(d[5]), "+f"(d[6]), "+f"(d[7]), "+f"(d[8]), "+f"(d[9]), "+f"(d[10]), "+f"(d[11]), "+f"(d[12]), "+f"(d[13]), "+f"(d[14]), "+f"(d[15]), "+f"(d[16]), "+f"(d[17]), "+f"(d[18]), "+f"(d[19]), "+f"(d[20]), "+f"(d[21]), "+f"(d[22]), "+f"(d[23]), "+f"(d[24]), "+f"(d[25]), "+f"(d[26]), "+f"(d[27]), "+f"(d[28]), "+f"(d[29]), "+f"(d[30]), "+f"(d[31]), "+f"(d[32]), "+f"(d[33]), "+f"(d[34]), "+f"(d[35]), "+f"(d[36]), "+f"(d[37]), "+f"(d[38]), "+f"(d[39]), "+f"(d[40]), "+f"(d[41]), "+f"(d[42]), "+f"(d[43]), "+f"(d[44]), "+f"(d[45]), "+f"(d[46]), "+f"(d[47]), "+f"(d[48]), "+f"(d[49]), "+f"(d[50]), "+f"(d[51]), "+f"(d[52]), "+f"(d[53]), "+f"(d[54]), "+f"(d[55]), "+f"(d[56]), "+f"(d[57]), "+f"(d[58]), "+f"(d[59]), "+f"(d[60]), "+f"(d[61]), "+f"(d[62]), "+f"(d[63])
    : "r"(abase), "n"(AI), "n"(BI));
}
template <uint32_t BI> __device__ __forceinline__ void wg_rs64(float (&d)[32], uint32_t a0, uint32_t a1, uint32_t a2, uint32_t a3) {
  asm volatile("{\n.reg .pred p;\n.reg .b64 db;\nsetp.ne.b32 p, 1, 0;\nmov.b64 db, {%36, 0x40000040};\n"
    "wgmma.mma_async.sync.aligned.m64n64k16.f32.bf16.bf16 "
    "{%0, %1, %2, %3, %4, %5, %6, %7, %8, %9, %10, %11, %12, %13, %14, %15, %16, %17, %18, %19, %20, %21, %22, %23, %24, %25, %26, %27, %28, %29, %30, %31}, {%32, %33, %34, %35}, db, p, 1, 1, 1;\n}\n"
    : "+f"(d[0]), "+f"(d[1]), "+f"(d[2]), "+f"(d[3]), "+f"(d[4]), "+f"(d[5]), "+f"(d[6]), "+f"(d[7]), "+f"(d[8]), "+f"(d[9]), "+f"(d[10]), "+f"(d[11]), "+f"(d[12]), "+f"(d[13]), "+f"(d[14]), "+f"(d[15]), "+f"(d[16]), "+f"(d[17]), "+f"(d[18]), "+f"(d[19]), "+f"(d[20]), "+f"(d[21]), "+f"(d[22]), "+f"(d[23]), "+f"(d[24]), "+f"(d[25]), "+f"(d[26]), "+f"(d[27]), "+f"(d[28]), "+f"(d[29]), "+f"(d[30]), "+f"(d[31])
    : "r"(a0), "r"(a1), "r"(a2), "r"(a3), "n"(BI));
}
template <uint32_t AI, uint32_t BI> __device__ __forceinline__ void wg_ss256_t01_z(float (&d)[128], uint32_t abase) {
  asm volatile("{\n.reg .pred p;\n.reg .b32 t;\n.reg .b64 da, db;\nsetp.ne.b32 p, 0, 0;\nadd.u32 t, %128, %129;\n"
    "mov.b64 da, {t, 0x40000040};\nmov.b64 db, {%130, 0x40000040};\n"
    "wgmma.mma_async.sync.aligned.m64n256k16.f32.bf16.bf16 "
    "{%0, %1, %2, %3, %4, %5, %6, %7, %8, %9, %10, %11, %12, %13, %14, %15, %16, %17, %18, %19, %20, %21, %22, %23, %24, %25, %26, %27, %28, %29, %30, %31, %32, %33, %34, %35, %36, %37, %38, %39, %40, %41, %42, %43, %44, %45, %46, %47, %48, %49, %50, %51, %52, %53, %54, %55, %56, %57, %58, %59, %60, %61, %62, %63, %64, %65, %66, %67, %68, %69, %70, %71, %72, %73, %74, %75, %76, %77, %78, %79, %80, %81, %82, %83, %84, %85, %86, %87, %88, %89, %90, %91, %92, %93, %94, %95, %96, %97, %98, %99, %100, %101, %102, %103, %104, %105, %106, %107, %108, %109, %110, %111, %112, %113, %114, %115, %116, %117, %118, %119, %120, %121, %122, %123, %124, %125, %126, %127}, da, db, p, 1, 1, 0, 1;\n}\n"
    : "=f"(d[0]), "=f"(d[1]), "=f"(d[2]), "=f"(d[3]), "=f"(d[4]), "=f"(d[5]), "=f"(d[6]), "=f"(d[7]), "=f"(d[8]), "=f"(d[9]), "=f"(d[10]), "=f"(d[11]), "=f"(d[12]), "=f"(d[13]), "=f"(d[14]), "=f"(d[15]), "=f"(d[16]), "=f"(d[17]), "=f"(d[18]), "=f"(d[19]), "=f"(d[20]), "=f"(d[21]), "=f"(d[22]), "=f"(d[23]), "=f"(d[24]), "=f"(d[25]), "=f"(d[26]), "=f"(d[27]), "=f"(d[28]), "=f"(d[29]), "=f"(d[30]), "=f"(d[31]), "=f"(d[32]), "=f"(d[33]), "=f"(d[34]), "=f"(d[35]), "=f"(d[36]), "=f"(d[37]), "=f"(d[38]), "=f"(d[39]), "=f"(d[40]), "=f"(d[41]), "=f"(d[42]), "=f"(d[43]), "=f"(d[44]), "=f"(d[45]), "=f"(d[46]), "=f"(d[47]), "=f"(d[48]), "=f"(d[49]), "=f"(d[50]), "=f"(d[51]), "=f"(d[52]), "=f"(d[53]), "=f"(d[54]), "=f"(d[55]), "=f"(d[56]), "=f"(d[57]), "=f"(d[58]), "=f"(d[59]), "=f"(d[60]), "=f"(d[61]), "=f"(d[62]), "=f"(d[63]), "=f"(d[64]), "=f"(d[65]), "=f"(d[66]), "=f"(d[67]), "=f"(d[68]), "=f"(d[69]), "=f"(d[70]), "=f"(d[71]), "=f"(d[72]), "=f"(d[73]), "=f"(d[74]), "=f"(d[75]), "=f"(d[76]), "=f"(d[77]), "=f"(d[78]), "=f"(d[79]), "=f"(d[80]), "=f"(d[81]), "=f"(d[82]), "=f"(d[83]), "=f"(d[84]), "=f"(d[85]), "=f"(d[86]), "=f"(d[87]), "=f"(d[88]), "=f"(d[89]), "=f"(d[90]), "=f"(d[91]), "=f"(d[92]), "=f"(d[93]), "=f"(d[94]), "=f"(d[95]), "=f"(d[96]), "=f"(d[97]), "=f"(d[98]), "=f"(d[99]), "=f"(d[100]), "=f"(d[101]), "=f"(d[102]), "=f"(d[103]), "=f"(d[104]), "=f"(d[105]), "=f"(d[106]), "=f"(d[107]), "=f"(d[108]), "=f"(d[109]), "=f"(d[110]), "=f"(d[111]), "=f"(d[112]), "=f"(d[113]), "=f"(d[114]), "=f"(d[115]), "=f"(d[116]), "=f"(d[117]), "=f"(d[118]), "=f"(d[119]), "=f"(d[120]), "=f"(d[121]), "=f"(d[122]), "=f"(d[123]), "=f"(d[124]), "=f"(d[125]), "=f"(d[126]), "=f"(d[127])
    : "r"(abase), "n"(AI), "n"(BI));
}
template <uint32_t AI, uint32_t BI> __device__ __forceinline__ void wg_ss128_t01_z(float (&d)[64], uint32_t abase) {
  asm volatile("{\n.reg .pred p;\n.reg .b32 t;\n.reg .b64 da, db;\nsetp.ne.b32 p, 0, 0;\nadd.u32 t, %64, %65;\n"
    "mov.b64 da, {t, 0x40000040};\nmov.b64 db, {%66, 0x40000040};\n"
    "wgmma.mma_async.sync.aligned.m64n128k16.f32.bf16.bf16 "
    "{%0, %1, %2, %3, %4, %5, %6, %7, %8, %9, %10, %11, %12, %13, %14, %15, %16, %17, %18, %19, %20, %21, %22, %23, %24, %25, %26, %27, %28, %29, %30, %31, %32, %33, %34, %35, %36, %37, %38, %39, %40, %41, %42, %43, %44, %45, %46, %47, %48, %49, %50, %51, %52, %53, %54, %55, %56, %57, %58, %59, %60, %61, %62, %63}, da, db, p, 1, 1, 0, 1;\n}\n"
    : "=f"(d[0]), "=f"(d[1]), "=f"(d[2]), "=f"(d[3]), "=f"(d[4]), "=f"(d[5]), "=f"(d[6]), "=f"(d[7]), "=f"(d[8]), "=f"(d[9]), "=f"(d[10]), "=f"(d[11]), "=f"(d[12]), "=f"(d[13]), "=f"(d[14]), "=f"(d[15]), "=f"(d[16]), "=f"(d[17]), "=f"(d[18]), "=f"(d[19]), "=f"(d[20]), "=f"(d[21]), "=f"(d[22]), "=f"(d[23]), "=f"(d[24]), "=f"(d[25]), "=f"(d[26]), "=f"(d[27]), "=f"(d[28]), "=f"(d[29]), "=f"(d[30]), "=f"(d[31]), "=f"(d[32]), "=f"(d[33]), "=f"(d[34]), "=f"(d[35]), "=f"(d[36]), "=f"(d[37]), "=f"(d[38]), "=f"(d[39]), "=f"(d[40]), "=f"(d[41]), "=f"(d[42]), "=f"(d[43]), "=f"(d[44]), "=f"(d[45]), "=f"(d[46]), "=f"(d[47]), "=f"(d[48]), "=f"(d[49]), "=f"(d[50]), "=f"(d[51]), "=f"(d[52]), "=f"(d[53]), "=f"(d[54]), "=f"(d[55]), "=f"(d[56]), "=f"(d[57]), "=f"(d[58]), "=f"(d[59]), "=f"(d[60]), "=f"(d[61]), "=f"(d[62]), "=f"(d[63])
    : "r"(abase), "n"(AI), "n"(BI));
}
template <uint32_t AI, uint32_t BI> __device__ __forceinline__ void wg_ss128_t10_z(float (&d)[64], uint32_t abase) {
  asm volatile("{\n.reg .pred p;\n.reg .b32 t;\n.reg .b64 da, db;\nsetp.ne.b32 p, 0, 0;\nadd.u32 t, %64, %65;\n"
    "mov.b64 da, {t, 0x40000040};\nmov.b64 db, {%66, 0x40000040};\n"
    "wgmma.mma_async.sync.aligned.m64n128k16.f32.bf16.bf16 "
    "{%0, %1, %2, %3, %4, %5, %6, %7, %8, %9, %10, %11, %12, %13, %14, %15, %16, %17, %18, %19, %20, %21, %22, %23, %24, %25, %26, %27, %28, %29, %30, %31, %32, %33, %34, %35, %36, %37, %38, %39, %40, %41, %42, %43, %44, %45, %46, %47, %48, %49, %50, %51, %52, %53, %54, %55, %56, %57, %58, %59, %60, %61, %62, %63}, da, db, p, 1, 1, 1, 0;\n}\n"
    : "=f"(d[0]), "=f"(d[1]), "=f"(d[2]), "=f"(d[3]), "=f"(d[4]), "=f"(d[5]), "=f"(d[6]), "=f"(d[7]), "=f"(d[8]), "=f"(d[9]), "=f"(d[10]), "=f"(d[11]), "=f"(d[12]), "=f"(d[13]), "=f"(d[14]), "=f"(d[15]), "=f"(d[16]), "=f"(d[17]), "=f"(d[18]), "=f"(d[19]), "=f"(d[20]), "=f"(d[21]), "=f"(d[22]), "=f"(d[23]), "=f"(d[24]), "=f"(d[25]), "=f"(d[26]), "=f"(d[27]), "=f"(d[28]), "=f"(d[29]), "=f"(d[30]), "=f"(d[31]), "=f"(d[32]), "=f"(d[33]), "=f"(d[34]), "=f"(d[35]), "=f"(d[36]), "=f"(d[37]), "=f"(d[38]), "=f"(d[39]), "=f"(d[40]), "=f"(d[41]), "=f"(d[42]), "=f"(d[43]), "=f"(d[44]), "=f"(d[45]), "=f"(d[46]), "=f"(d[47]), "=f"(d[48]), "=f"(d[49]), "=f"(d[50]), "=f"(d[51]), "=f"(d[52]), "=f"(d[53]), "=f"(d[54]), "=f"(d[55]), "=f"(d[56]), "=f"(d[57]), "=f"(d[58]), "=f"(d[59]), "=f"(d[60]), "=f"(d[61]), "=f"(d[62]), "=f"(d[63])
    : "r"(abase), "n"(AI), "n"(BI));
}
template <uint32_t BI> __device__ __forceinline__ void wg_rs64_z(float (&d)[32], uint32_t a0, uint32_t a1, uint32_t a2, uint32_t a3) {
  asm volatile("{\n.reg .pred p;\n.reg .b64 db;\nsetp.ne.b32 p, 0, 0;\nmov.b64 db, {%36, 0x40000040};\n"
    "wgmma.mma_async.sync.aligned.m64n64k16.f32.bf16.bf16 "
    "{%0, %1, %2, %3, %4, %5, %6, %7, %8, %9, %10, %11, %12, %13, %14, %15, %16, %17, %18, %19, %20, %21, %22, %23, %24, %25, %26, %27, %28, %29, %30, %31}, {%32, %33, %34, %35}, db, p, 1, 1, 1;\n}\n"
    : "=f"(d[0]), "=f"(d[1]), "=f"(d[2]), "=f"(d[3]), "=f"(d[4]), "=f"(d[5]), "=f"(d[6]), "=f"(d[7]), "=f"(d[8]), "=f"(d[9]), "=f"(d[10]), "=f"(d[11]), "=f"(d[12]), "=f"(d[13]), "=f"(d[14]), "=f"(d[15]), "=f"(d[16]), "=f"(d[17]), "=f"(d[18]), "=f"(d[19]), "=f"(d[20]), "=f"(d[21]), "=f"(d[22]), "=f"(d[23]), "=f"(d[24]), "=f"(d[25]), "=f"(d[26]), "=f"(d[27]), "=f"(d[28]), "=f"(d[29]), "=f"(d[30]), "=f"(d[31])
    : "r"(a0), "r"(a1), "r"(a2), "r"(a3), "n"(BI));
}

namespace {

constexpr uint32_t SB = 1024;
constexpr uint32_t XB = SB;
constexpr uint32_t RB = SB + 131072;
constexpr uint32_t MISC = RB + 98304;
constexpr uint32_t ZS = MISC;
constexpr uint32_t BAR = MISC + 1024;
constexpr uint32_t B_XF = BAR;
constexpr uint32_t B_SF = B_XF + 8 * 8;
constexpr uint32_t B_EF = B_SF + 20 * 8;
constexpr uint32_t B_KV = B_EF + 8 * 8;
constexpr uint32_t B_EP = B_KV + 8;
constexpr uint32_t B_ZK = B_EP + 8;
constexpr uint32_t B_SE = B_ZK + 8;
constexpr uint32_t B_EE = B_SE + 20 * 8;
constexpr uint32_t B_OD = B_EE + 8 * 8;
constexpr uint32_t B_KD = B_OD + 8;
constexpr uint32_t EPS = B_KD + 8;
constexpr int SMEM_BYTES = 131072 + 98304 + 2048;
constexpr int NTHREADS = 384;

__host__ __device__ constexpr uint32_t ring(int s) { return RB + ((s + 2) % 3) * 32768; }
__host__ __device__ constexpr uint32_t eslot_ffn(int i) { return SB + ((i & 3) == 0 ? 0u : (i & 3) == 1 ? 40960u : (i & 3) == 2 ? 163840u : 81920u); }
__host__ __device__ constexpr uint32_t eslot_att(int i) {
  return SB + ((i % 6) == 0 ? 32768u : (i % 6) == 1 ? 163840u : (i % 6) == 2 ? 65536u : (i % 6) == 3 ? 196608u : (i % 6) == 4 ? 98304u : 131072u);
}
__host__ __device__ constexpr uint32_t stg_ffn(int i) { return SB + 122880u + (i & 1) * 16384u; }
__host__ __device__ constexpr uint32_t stg_att(int i) { return SB + ((i & 1) ? 0u : 16384u); }

struct Params {
  CUtensorMap x, kv, q, g1, u1, g2, u2, wo, wda, wdf, out;
};

__device__ float g_kv[2][4][4352];
__device__ unsigned g_kvcnt[4 * 32];
__device__ unsigned g_zcnt[16 * 32];
#define TS(w, i) do {} while (0)

__device__ __forceinline__ void mbar_init(uint32_t bar, int cnt) { asm volatile("mbarrier.init.shared::cta.b64 [%0], %1;" ::"r"(bar), "r"(cnt)); }
__device__ __forceinline__ void mbar_expect(uint32_t bar, uint32_t bytes) {
  asm volatile("mbarrier.arrive.expect_tx.shared::cta.b64 _, [%0], %1;" ::"r"(bar), "r"(bytes) : "memory");
}
__device__ __forceinline__ void mbar_arrive(uint32_t bar) { asm volatile("mbarrier.arrive.shared::cta.b64 _, [%0];" ::"r"(bar) : "memory"); }
__device__ __forceinline__ void mbar_wait(uint32_t bar) {
  asm volatile(
      "{\n.reg .pred p;\n.reg .u32 c;\nmov.u32 c, 0;\n"
      "LW%=:\nmbarrier.try_wait.parity.shared::cta.b64 p, [%0], 0;\n@p bra LD%=;\n"
      "add.u32 c, c, 1;\nsetp.lt.u32 p, c, 2097152;\n@p bra LW%=;\ntrap;\nLD%=:\n}" ::"r"(bar) : "memory");
}
__device__ __forceinline__ void flag_wait(const unsigned* p, unsigned target) {
  asm volatile(
      "{\n.reg .pred p;\n.reg .u32 c, v;\nmov.u32 c, 0;\n"
      "LW%=:\nld.acquire.gpu.global.u32 v, [%0];\nsub.u32 v, v, %1;\nsetp.ge.s32 p, v, 0;\n@p bra LD%=;\n"
      "add.u32 c, c, 1;\nsetp.lt.u32 p, c, 2097152;\n@p bra LW%=;\ntrap;\nLD%=:\n}" ::"l"(p), "r"(target) : "memory");
}
__device__ __forceinline__ void tma2(uint32_t dst, const CUtensorMap* m, uint32_t bar, int c0, int c1) {
  asm volatile("cp.async.bulk.tensor.2d.shared::cluster.global.mbarrier::complete_tx::bytes [%0], [%1, {%3,%4}], [%2];" ::"r"(dst), "l"(m), "r"(bar), "r"(c0), "r"(c1) : "memory");
}
__device__ __forceinline__ void tma3(uint32_t dst, const CUtensorMap* m, uint32_t bar, int c1, int c2) {
  asm volatile("cp.async.bulk.tensor.3d.shared::cluster.global.mbarrier::complete_tx::bytes [%0], [%1, {%3,%4,%5}], [%2];" ::"r"(dst), "l"(m), "r"(bar), "r"(0), "r"(c1), "r"(c2) : "memory");
}
__device__ __forceinline__ void tma4(uint32_t dst, const CUtensorMap* m, uint32_t bar, int c1, int c2, int c3) {
  asm volatile("cp.async.bulk.tensor.4d.shared::cluster.global.mbarrier::complete_tx::bytes [%0], [%1, {%3,%4,%5,%6}], [%2];" ::"r"(dst), "l"(m), "r"(bar), "r"(0), "r"(c1), "r"(c2), "r"(c3) : "memory");
}
__device__ __forceinline__ void bulk_g2s(uint32_t dst, const void* src, uint32_t bytes, uint32_t bar) {
  asm volatile("cp.async.bulk.shared::cluster.global.mbarrier::complete_tx::bytes [%0], [%1], %2, [%3];" ::"r"(dst), "l"(src), "r"(bytes), "r"(bar) : "memory");
}
__device__ __forceinline__ void prefetch_tm(const CUtensorMap* m) { asm volatile("prefetch.tensormap [%0];" ::"l"(m) : "memory"); }
__host__ __device__ constexpr uint32_t dlo(uint32_t addr, uint32_t lbo) { return ((addr & 0x3FFFF) >> 4) | ((lbo >> 4) << 16); }
template <int I, int N, class F> __device__ __forceinline__ void sfor(F&& f) {
  if constexpr (I < N) { f(std::integral_constant<int, I>{}); sfor<I + 1, N>(f); }
}
#define WG_FENCE() asm volatile("wgmma.fence.sync.aligned;" ::: "memory")
#define WG_COMMIT() asm volatile("wgmma.commit_group.sync.aligned;" ::: "memory")
#define WG_WAIT(n) asm volatile("wgmma.wait_group.sync.aligned %0;" ::"n"(n) : "memory")
template <int N> __device__ __forceinline__ void pin(float (&a)[N]) {
#pragma unroll
  for (int i = 0; i < N; i++) asm volatile("" : "+f"(a[i])::"memory");
}
template <int N> __device__ __forceinline__ void pin(uint32_t (&a)[N]) {
#pragma unroll
  for (int i = 0; i < N; i++) asm volatile("" : "+r"(a[i])::"memory");
}
__device__ __forceinline__ uint32_t pk(float lo, float hi) { uint32_t r; asm("cvt.rn.bf16x2.f32 %0, %1, %2;" : "=r"(r) : "f"(hi), "f"(lo)); return r; }
__device__ __forceinline__ float blo(uint32_t v) { return __uint_as_float(v << 16); }
__device__ __forceinline__ float bhi(uint32_t v) { return __uint_as_float(v & 0xffff0000u); }
__device__ __forceinline__ uint32_t movm(uint32_t a) { uint32_t d; asm volatile("movmatrix.sync.aligned.m8n8.trans.b16 %0, %1;" : "=r"(d) : "r"(a)); return d; }
__device__ __forceinline__ uint32_t hmax2(uint32_t a, uint32_t b) { uint32_t d; asm("max.bf16x2 %0, %1, %2;" : "=r"(d) : "r"(a), "r"(b)); return d; }
__device__ __forceinline__ float ex2(float x) { float y; asm("ex2.approx.ftz.f32 %0, %1;" : "=f"(y) : "f"(x)); return y; }
__device__ __forceinline__ float rcp(float x) { float y; asm("rcp.approx.ftz.f32 %0, %1;" : "=f"(y) : "f"(x)); return y; }
__device__ __forceinline__ void mma(float (&c)[4], uint32_t a0, uint32_t a1, uint32_t a2, uint32_t a3, uint32_t b0, uint32_t b1) {
  asm volatile("mma.sync.aligned.m16n8k16.row.col.f32.bf16.bf16.f32 {%0,%1,%2,%3}, {%4,%5,%6,%7}, {%8,%9}, {%0,%1,%2,%3};"
      : "+f"(c[0]), "+f"(c[1]), "+f"(c[2]), "+f"(c[3]) : "r"(a0), "r"(a1), "r"(a2), "r"(a3), "r"(b0), "r"(b1));
}
__device__ __forceinline__ void mma0(float (&c)[4], uint32_t a0, uint32_t a1, uint32_t a2, uint32_t a3, uint32_t b0, uint32_t b1) {
  asm volatile("mma.sync.aligned.m16n8k16.row.col.f32.bf16.bf16.f32 {%0,%1,%2,%3}, {%4,%5,%6,%7}, {%8,%9}, {%10,%10,%10,%10};"
      : "=f"(c[0]), "=f"(c[1]), "=f"(c[2]), "=f"(c[3]) : "r"(a0), "r"(a1), "r"(a2), "r"(a3), "r"(b0), "r"(b1), "f"(0.f));
}
__device__ __forceinline__ uint4 lds128(uint32_t a) { uint4 v; asm volatile("ld.shared.v4.u32 {%0,%1,%2,%3}, [%4];" : "=r"(v.x), "=r"(v.y), "=r"(v.z), "=r"(v.w) : "r"(a) : "memory"); return v; }
__device__ __forceinline__ void stsm4(uint32_t a, uint32_t r0, uint32_t r1, uint32_t r2, uint32_t r3) {
  asm volatile("stmatrix.sync.aligned.m8n8.x4.shared.b16 [%0], {%1,%2,%3,%4};" ::"r"(a), "r"(r0), "r"(r1), "r"(r2), "r"(r3) : "memory");
}
__device__ __forceinline__ float dot8(uint4 x, uint4 w, float acc) {
  acc = fmaf(blo(x.x), blo(w.x), acc); acc = fmaf(bhi(x.x), bhi(w.x), acc);
  acc = fmaf(blo(x.y), blo(w.y), acc); acc = fmaf(bhi(x.y), bhi(w.y), acc);
  acc = fmaf(blo(x.z), blo(w.z), acc); acc = fmaf(bhi(x.z), bhi(w.z), acc);
  acc = fmaf(blo(x.w), blo(w.w), acc); acc = fmaf(bhi(x.w), bhi(w.w), acc);
  return acc;
}

template <bool ZSUM>
__device__ __forceinline__ void dual_softmax(const float (&c0)[4], const float (&c1)[4], uint32_t (&P)[8], float (&z)[8]) {
  constexpr float L = 1.4426950408889634f;
  uint32_t wa = pk(fmaxf(fmaxf(c0[0], c0[1]), fmaxf(c1[0], c1[1])), -fminf(fminf(c0[0], c0[1]), fminf(c1[0], c1[1])));
  uint32_t wb = pk(fmaxf(fmaxf(c0[2], c0[3]), fmaxf(c1[2], c1[3])), -fminf(fminf(c0[2], c0[3]), fminf(c1[2], c1[3])));
  wa = hmax2(wa, __shfl_xor_sync(0xffffffffu, wa, 1)); wb = hmax2(wb, __shfl_xor_sync(0xffffffffu, wb, 1));
  wa = hmax2(wa, __shfl_xor_sync(0xffffffffu, wa, 2)); wb = hmax2(wb, __shfl_xor_sync(0xffffffffu, wb, 2));
  const float pa = -L * blo(wa), na = -L * bhi(wa), pb = -L * blo(wb), nb = -L * bhi(wb);
  float ep[8], en[8];
#pragma unroll
  for (int i = 0; i < 4; i++) {
    ep[i] = ex2(fmaf(c0[i], L, i < 2 ? pa : pb)); ep[4 + i] = ex2(fmaf(c1[i], L, i < 2 ? pa : pb));
    en[i] = ex2(fmaf(c0[i], -L, i < 2 ? na : nb)); en[4 + i] = ex2(fmaf(c1[i], -L, i < 2 ? na : nb));
  }
  float sp[4], sn[4];
  mma0(sp, pk(ep[0], ep[1]), pk(ep[2], ep[3]), pk(ep[4], ep[5]), pk(ep[6], ep[7]), 0x3f803f80u, 0x3f803f80u);
  mma0(sn, pk(en[0], en[1]), pk(en[2], en[3]), pk(en[4], en[5]), pk(en[6], en[7]), 0x3f803f80u, 0x3f803f80u);
  const float ra = rcp(sp[0] * sn[0]), rb = rcp(sp[2] * sn[2]);
  const float rpa = ra * sn[0], rna = ra * sp[0], rpb = rb * sn[2], rnb = rb * sp[2];
#pragma unroll
  for (int i = 0; i < 8; i++) { ep[i] *= (i & 2) ? rpb : rpa; en[i] *= (i & 2) ? rnb : rna; }
#pragma unroll
  for (int i = 0; i < 4; i++) { P[i] = pk(ep[2 * i], ep[2 * i + 1]); P[4 + i] = pk(en[2 * i], en[2 * i + 1]); }
  if (ZSUM) {
    z[0] += ep[0] + ep[2]; z[1] += ep[1] + ep[3]; z[2] += ep[4] + ep[6]; z[3] += ep[5] + ep[7];
    z[4] += en[0] + en[2]; z[5] += en[1] + en[3]; z[6] += en[4] + en[6]; z[7] += en[5] + en[7];
  }
}

__device__ __forceinline__ void load_wphi(uint32_t (&w)[4], const __nv_bfloat16* wphi, int head, int lane) {
  const uint32_t* p = reinterpret_cast<const uint32_t*>(wphi + head * 256 + (lane >> 2) * 16 + (lane & 3) * 2);
  w[0] = __ldg(p); w[1] = __ldg(p + 64); w[2] = __ldg(p + 4); w[3] = __ldg(p + 68);
}

template <int NB, int N, int M>
__device__ __forceinline__ void gu_pack(const float (&a)[N], uint32_t (&h)[M], int off, float sa, float sb) {
#pragma unroll
  for (int i = 0; i < NB * 16; i++) {
    const float s = (i & 1) ? sb : sa;
    h[off + i] = pk(a[2 * i] * a[NB * 32 + 2 * i] * s, a[2 * i + 1] * a[NB * 32 + 2 * i + 1] * s);
  }
#pragma unroll
  for (int i = 0; i < NB * 16; i++) asm volatile("" : "+r"(h[off + i])::"memory");
}

template <int S, int T, bool REUSE = false>
__device__ __forceinline__ void issue128(float (&acc)[64], uint32_t xa, uint32_t zero = 0) {
  mbar_wait(B_SF + 8 * S);
  WG_FENCE();
  sfor<0, 8>([&](auto kc) {
    constexpr int k = kc.value;
    constexpr uint32_t AI = dlo(XB + (2 * T + (k >> 2)) * 16384 + (k & 3) * 32, 16), BI = dlo(ring(S) + k * 2048, 16384);
    if constexpr (T == 0 && k == 0 && REUSE) wg_ss128_t01_p<AI, BI>(acc, xa, zero);
    else if constexpr (T == 0 && k == 0) wg_ss128_t01_z<AI, BI>(acc, xa); else wg_ss128_t01<AI, BI>(acc, xa);
  });
  WG_COMMIT();
}
template <int K0, int K1, bool Z, uint32_t SLOT, int M>
__device__ __forceinline__ void issue_p2(float (&acc)[32], const uint32_t (&a)[M]) {
  WG_FENCE();
  sfor<K0, K1>([&](auto kc) {
    constexpr int k = kc.value;
    constexpr uint32_t BI = dlo(SLOT + k * 2048, 8192);
    if constexpr (Z && k == K0) wg_rs64_z<BI>(acc, a[4 * k], a[4 * k + 1], a[4 * k + 2], a[4 * k + 3]);
    else wg_rs64<BI>(acc, a[4 * k], a[4 * k + 1], a[4 * k + 2], a[4 * k + 3]);
  });
  WG_COMMIT();
}
template <int I>
__device__ __forceinline__ void out_tile(float (&c)[32], uint32_t stg, const CUtensorMap* tm, int col, int row, int lane) {
  pin(c);
  uint32_t p[16];
#pragma unroll
  for (int q = 0; q < 16; q++) p[q] = pk(c[2 * q], c[2 * q + 1]);
  if (I >= 2) { if (lane == 0) asm volatile("cp.async.bulk.wait_group.read 1;" ::: "memory"); __syncwarp(); }
  const int t = lane >> 3, r = lane & 7;
  const uint32_t rowa = stg + ((t & 1) * 8 + r) * 128;
#pragma unroll
  for (int q = 0; q < 4; q++) stsm4(rowa + (((2 * q + (t >> 1)) ^ r) << 4), p[4 * q], p[4 * q + 1], p[4 * q + 2], p[4 * q + 3]);
  asm volatile("fence.proxy.async.shared::cta;" ::: "memory");
  __syncwarp();
  if (lane == 0) {
    asm volatile("cp.reduce.async.bulk.tensor.2d.global.shared::cta.add.tile.bulk_group [%0, {%2,%3}], [%1];" ::"l"(tm), "r"(stg), "r"(col), "r"(row) : "memory");
    asm volatile("cp.async.bulk.commit_group;" ::: "memory");
  }
}

#define REL(bar) do { if (lane == 0) mbar_arrive(bar); } while (0)

template <bool ATT, int I, int M>
__device__ __forceinline__ void p2_step(float (&cur)[32], float (&prev)[32], const uint32_t (&a)[M], const CUtensorMap* tmo, int j, int row0, int warp, int lane) {
  mbar_wait(B_EF + 8 * I);
  issue_p2<0, M / 4, true, (ATT ? eslot_att(I) : eslot_ffn(I))>(cur, a);
  WG_WAIT(1);
  REL(B_EE + 8 * (I - 1));
  TS(warp >> 2, 24 + I);
  if (I == 1) mbar_wait(B_ZK);
  if (I == 1 && !ATT) mbar_wait(B_SE + 8 * 19);
  if (I == 2 && ATT) mbar_wait(B_OD);
  out_tile<I - 1>(prev, (ATT ? stg_att(I - 1) : stg_ffn(I - 1)) + warp * 2048, tmo, ((j + I - 1) & 7) * 64, row0, lane);
}
template <bool ATT, int M>
__device__ __forceinline__ void p2_rest(float (&pa)[32], float (&pb)[32], const uint32_t (&a)[M], const CUtensorMap* tmo, int j, int row0, int warp, int lane) {
  p2_step<ATT, 1>(pb, pa, a, tmo, j, row0, warp, lane);
  p2_step<ATT, 2>(pa, pb, a, tmo, j, row0, warp, lane);
  p2_step<ATT, 3>(pb, pa, a, tmo, j, row0, warp, lane);
  p2_step<ATT, 4>(pa, pb, a, tmo, j, row0, warp, lane);
  p2_step<ATT, 5>(pb, pa, a, tmo, j, row0, warp, lane);
  p2_step<ATT, 6>(pa, pb, a, tmo, j, row0, warp, lane);
  p2_step<ATT, 7>(pb, pa, a, tmo, j, row0, warp, lane);
  WG_WAIT(0);
  TS(warp >> 2, 32);
  out_tile<7>(pb, (ATT ? stg_att(7) : stg_ffn(7)) + warp * 2048, tmo, ((j + 7) & 7) * 64, row0, lane);
  if (lane == 0) asm volatile("cp.async.bulk.wait_group.read 0;" ::: "memory");
  TS(warp >> 2, 33);
}

template <int S>
__device__ __forceinline__ void gate_chunk(float& ga, float& gb, uint32_t gx, uint32_t c0, const uint4* gw) {
  const uint4 w0 = __ldg(gw + S * 8 + c0), w1 = __ldg(gw + S * 8 + (c0 ^ 4));
  const uint32_t a = gx + S * 16384;
  const uint4 x0 = lds128(a), x1 = lds128(a ^ 64), x2 = lds128(a + 1024), x3 = lds128((a ^ 64) + 1024);
  ga = dot8(x1, w1, dot8(x0, w0, ga));
  gb = dot8(x3, w1, dot8(x2, w0, gb));
  asm volatile("" : "+f"(ga), "+f"(gb)::"memory");
}

template <bool ATT, int S>
__device__ __forceinline__ void t1_step(float (&acc)[128], uint32_t xa, int wg, float& ga, float& gb, uint32_t gx, uint32_t c0, const uint4* gw, int warp, int lane) {
  mbar_wait(B_XF + 8 * S);
  mbar_wait(B_SF + 8 * S);
  WG_FENCE();
  if (ATT) {
    float (&ak)[64] = *reinterpret_cast<float (*)[64]>(&acc[0]);
    float (&av)[64] = *reinterpret_cast<float (*)[64]>(&acc[64]);
    sfor<0, 4>([&](auto kc) {
      constexpr int k = kc.value;
      constexpr uint32_t BI = dlo(XB + S * 16384 + k * 32, 16), KI = dlo(ring(S) + k * 2048, 8192), VI = dlo(ring(S) + 16384 + k * 2048, 8192);
      if constexpr (S == 0 && k == 0) { wg_ss128_t10_z<KI, BI>(ak, xa); wg_ss128_t10_z<VI, BI>(av, xa); }
      else { wg_ss128_t10<KI, BI>(ak, xa); wg_ss128_t10<VI, BI>(av, xa); }
    });
  } else {
    sfor<0, 4>([&](auto kc) {
      constexpr int k = kc.value;
      constexpr uint32_t AI = dlo(XB + S * 16384 + k * 32, 16), BI = dlo(ring(S) + k * 2048, 8192);
      if constexpr (S == 0 && k == 0) wg_ss256_t01_z<AI, BI>(acc, xa); else wg_ss256_t01<AI, BI>(acc, xa);
    });
  }
  WG_COMMIT();
  if (S > 0) { WG_WAIT(1); REL(B_SE + 8 * (S > 0 ? S - 1 : 0)); }
  TS(wg, 2 + S);
  gate_chunk<S>(ga, gb, gx, c0, gw);
}
template <bool ATT>
__device__ __forceinline__ void t1_all(float (&acc)[128], uint32_t xa, int wg, float& ga, float& gb, const __nv_bfloat16* gate_w, int warp, int lane) {
  const int g = lane >> 2;
  const uint32_t c0 = (lane & 3) | ((g & 1) << 2);
  const uint32_t gx = XB + (warp * 16 + g) * 128 + ((c0 ^ g) << 4);
  const uint4* gw = reinterpret_cast<const uint4*>(gate_w);
  ga = 0.f; gb = 0.f;
  t1_step<ATT, 0>(acc, xa, wg, ga, gb, gx, c0, gw, warp, lane);
  t1_step<ATT, 1>(acc, xa, wg, ga, gb, gx, c0, gw, warp, lane);
  t1_step<ATT, 2>(acc, xa, wg, ga, gb, gx, c0, gw, warp, lane);
  t1_step<ATT, 3>(acc, xa, wg, ga, gb, gx, c0, gw, warp, lane);
  t1_step<ATT, 4>(acc, xa, wg, ga, gb, gx, c0, gw, warp, lane);
  t1_step<ATT, 5>(acc, xa, wg, ga, gb, gx, c0, gw, warp, lane);
  t1_step<ATT, 6>(acc, xa, wg, ga, gb, gx, c0, gw, warp, lane);
  t1_step<ATT, 7>(acc, xa, wg, ga, gb, gx, c0, gw, warp, lane);
  ga += __shfl_xor_sync(0xffffffffu, ga, 1); gb += __shfl_xor_sync(0xffffffffu, gb, 1);
  ga += __shfl_xor_sync(0xffffffffu, ga, 2); gb += __shfl_xor_sync(0xffffffffu, gb, 2);
  ga = rcp(1.f + ex2(-1.4426950408889634f * ga)); gb = rcp(1.f + ex2(-1.4426950408889634f * gb));
}

#define STEP128R(S, ACC) do { issue128<S, 0, true>(ACC, xa, blockIdx.y); WG_WAIT(1); REL(B_SE + 8 * ((S) - 1)); TS(wg, 2 + (S)); } while (0)
#define STEP128(S, T, ACC) do { issue128<S, T>(ACC, xa); WG_WAIT(1); REL(B_SE + 8 * ((S) - 1)); TS(wg, 2 + (S)); } while (0)

template <int T0>
__device__ __forceinline__ void k_chunk(const uint32_t (&kT)[32], const uint32_t (&vT)[32], const uint32_t (&wk)[4], float (&kv)[4][4], float (&z)[8]) {
#pragma unroll
  for (int t = T0; t < T0 + 2; t++) {
    const uint32_t a0 = movm(kT[4 * t]), a1 = movm(kT[4 * t + 2]), a2 = movm(kT[4 * t + 1]), a3 = movm(kT[4 * t + 3]);
    float c0[4], c1[4];
    mma0(c0, a0, a1, a2, a3, wk[0], wk[1]);
    mma0(c1, a0, a1, a2, a3, wk[2], wk[3]);
    uint32_t P[8];
    dual_softmax<true>(c0, c1, P, z);
#pragma unroll
    for (int c = 0; c < 4; c++) {
      const uint32_t b0 = movm(P[2 * c]), b1 = movm(P[2 * c + 1]);
      if (t == 0) mma0(kv[c], vT[4 * t], vT[4 * t + 1], vT[4 * t + 2], vT[4 * t + 3], b0, b1);
      else mma(kv[c], vT[4 * t], vT[4 * t + 1], vT[4 * t + 2], vT[4 * t + 3], b0, b1);
    }
  }
  pin(z);
}
template <int H0>
__device__ __forceinline__ void q_chunk(const uint32_t (&qa)[32], const uint32_t (&w0)[4], const uint32_t (&w1)[4], uint32_t (&phi)[8][8]) {
  float zd[8];
#pragma unroll
  for (int h = H0; h < H0 + 2; h++) {
    const uint32_t (&w)[4] = (h == H0) ? w0 : w1;
    float c0[4], c1[4];
    mma0(c0, qa[4 * h], qa[4 * h + 1], qa[4 * h + 2], qa[4 * h + 3], movm(w[0]), movm(w[1]));
    mma0(c1, qa[4 * h], qa[4 * h + 1], qa[4 * h + 2], qa[4 * h + 3], movm(w[2]), movm(w[3]));
    dual_softmax<false>(c0, c1, phi[h], zd);
    pin(phi[h]);
  }
}
template <int H0, int NH>
__device__ __forceinline__ void o_chunk(const uint32_t (&phi)[8][8], uint32_t (&a)[64], float ga, float gb, int lane) {
#pragma unroll
  for (int h = H0; h < H0 + NH; h++) {
    uint4 k[4];
#pragma unroll
    for (int c = 0; c < 4; c++) k[c] = lds128(XB + h * 2048 + c * 512 + lane * 16);
    const uint4 z0 = lds128(ZS + h * 128 + (lane & 3) * 32), z1 = lds128(ZS + h * 128 + (lane & 3) * 32 + 16);
#define F(x) __uint_as_float(x)
    float n0[4], n1[4], dn[4];
    mma0(n0, phi[h][0], phi[h][1], phi[h][2], phi[h][3], pk(F(k[0].x), F(k[0].y)), pk(F(k[1].x), F(k[1].y)));
    mma0(n1, phi[h][0], phi[h][1], phi[h][2], phi[h][3], pk(F(k[0].z), F(k[0].w)), pk(F(k[1].z), F(k[1].w)));
    mma0(dn, phi[h][0], phi[h][1], phi[h][2], phi[h][3], pk(F(z0.x), F(z0.y)), pk(F(z0.z), F(z0.w)));
    mma(n0, phi[h][4], phi[h][5], phi[h][6], phi[h][7], pk(F(k[2].x), F(k[2].y)), pk(F(k[3].x), F(k[3].y)));
    mma(n1, phi[h][4], phi[h][5], phi[h][6], phi[h][7], pk(F(k[2].z), F(k[2].w)), pk(F(k[3].z), F(k[3].w)));
    mma(dn, phi[h][4], phi[h][5], phi[h][6], phi[h][7], pk(F(z1.x), F(z1.y)), pk(F(z1.z), F(z1.w)));
#undef F
    const float sa = ga * rcp(dn[0] + 1e-6f), sb = gb * rcp(dn[2] + 1e-6f);
    a[4 * h] = pk(n0[0] * sa, n0[1] * sa); a[4 * h + 1] = pk(n0[2] * sb, n0[3] * sb);
    a[4 * h + 2] = pk(n1[0] * sa, n1[1] * sa); a[4 * h + 3] = pk(n1[2] * sb, n1[3] * sb);
#pragma unroll
    for (int i = 0; i < 4; i++) asm volatile("" : "+r"(a[4 * h + i])::"memory");
  }
}

__global__ void __launch_bounds__(NTHREADS, 1)
fused_kernel(const __grid_constant__ Params P, const __nv_bfloat16* __restrict__ wphi, const __nv_bfloat16* __restrict__ gate_w, __nv_bfloat16* out) {
  extern __shared__ __align__(1024) char smem_raw[];
  const int warp = __shfl_sync(0xffffffffu, threadIdx.x >> 5, 0), lane = threadIdx.x & 31;
  const int m = blockIdx.x & 15, j = blockIdx.x >> 4;
  const bool att = j < 4;
  if ((uint32_t)__cvta_generic_to_shared(smem_raw) != SB) return;
  TS(warp >> 2, 0);
  if (warp == 9 && lane == 0) {
#pragma unroll
    for (int i = 3; i < 31; i++) mbar_init(B_SF + 8 * i, 1);
  }
  if (warp == 10 && lane == 0) {
#pragma unroll
    for (int i = 0; i < 30; i++) mbar_init(B_SE + 8 * i, 8);
  }
  if (warp == 8) {
    if (lane == 0) {
#pragma unroll
      for (int i = 0; i < 11; i++) mbar_init(B_XF + 8 * i, 1);
      asm volatile("fence.proxy.async.shared::cta;" ::: "memory");
      const int fb = 8 + 5 * (j - 4);
#pragma unroll
      for (int s = 0; s < 8; s++) {
        mbar_expect(B_XF + 8 * s, 16384);
        tma2(XB + s * 16384, &P.x, B_XF + 8 * s, s * 64, m * 128);
        if (s < 3) {
          mbar_expect(B_SF + 8 * s, 32768);
          if (att) tma4(ring(s), &P.kv, B_SF + 8 * s, s * 64, 2 * j, 1);
          else { tma3(ring(s), &P.g1, B_SF + 8 * s, s * 64, fb); tma3(ring(s) + 16384, &P.u1, B_SF + 8 * s, s * 64, fb); }
        }
      }
    }
  }
  __syncthreads();
  if (warp >= 8) {
    asm volatile("setmaxnreg.dec.sync.aligned.u32 24;");
    if (warp == 8 && lane == 0) {
      const int fb = 8 + 5 * (j - 4);
      asm volatile("fence.proxy.async.shared::cta;" ::: "memory");
      if (att) { prefetch_tm(&P.q); prefetch_tm(&P.wo); prefetch_tm(&P.wda); } else prefetch_tm(&P.wdf);
      prefetch_tm(&P.g2); prefetch_tm(&P.u2); prefetch_tm(&P.out);
#pragma unroll 1
      for (int s = 3; s < 20; s++) {
        mbar_wait(B_SE + 8 * (s - 3));
        const uint32_t dst = RB + ((s + 2) % 3) * 32768, bar = B_SF + 8 * s;
        mbar_expect(bar, 32768);
        if (s < 8) {
          if (att) tma4(dst, &P.kv, bar, s * 64, 2 * j, 1);
          else { tma3(dst, &P.g1, bar, s * 64, fb); tma3(dst + 16384, &P.u1, bar, s * 64, fb); }
        } else {
          const int tl = (s - 8) >> 2, r = (s & 3) * 128;
          if (att && tl == 0) tma4(dst, &P.q, bar, r, 2 * j, 0);
          else { const int b = att ? 2 * j + tl - 1 : fb + 2 + tl; tma3(dst, &P.g2, bar, r, b); tma3(dst + 16384, &P.u2, bar, r, b); }
        }
      }
      if (att) {
#pragma unroll
        for (int i = 0; i < 8; i++) {
          if (i < 6) { if ((i & 1) == 0) mbar_wait(B_SE + 8 * (17 + i / 2)); } else mbar_wait(B_EE + 8 * (i - 6));
          const int col = ((j + i) & 7) * 64;
          mbar_expect(B_EF + 8 * i, 32768);
          tma2(eslot_att(i), &P.wo, B_EF + 8 * i, col, j * 128);
          tma2(eslot_att(i) + 16384, &P.wda, B_EF + 8 * i, col, j * 128);
        }
      } else {
#pragma unroll
        for (int i = 0; i < 8; i++) {
          if (i == 0) mbar_wait(B_SE + 8 * 17); else if (i == 1) mbar_wait(B_SE + 8 * 18); else if (i == 3) mbar_wait(B_SE + 8 * 19);
          else if (i >= 4) mbar_wait(B_EE + 8 * (i - 4));
          const int col = ((j + i) & 7) * 64;
          mbar_expect(B_EF + 8 * i, 40960);
          tma2(eslot_ffn(i), &P.wdf, B_EF + 8 * i, col, fb * 64);
          tma2(eslot_ffn(i) + 20480, &P.wdf, B_EF + 8 * i, col, fb * 64 + 160);
        }
      }
    } else if (warp == 9) {
      unsigned ep;
      asm volatile("ld.relaxed.gpu.global.u32 %0, [%1];" : "=r"(ep) : "l"(&g_zcnt[m * 32]) : "memory");
      uint4* o = reinterpret_cast<uint4*>(out + (m * 128 + j * 16) * 512) + lane;
#pragma unroll 8
      for (int i = 0; i < 32; i++) o[i * 32] = make_uint4(0, 0, 0, 0);
      ep >>= 3;
      if (lane == 0) { asm volatile("st.shared.u32 [%0], %1;" ::"r"(EPS), "r"(ep) : "memory"); mbar_arrive(B_EP); }
      if (att) {
        uint4* z = reinterpret_cast<uint4*>(g_kv[(ep + 1) & 1][j]) + m * 68;
        for (int i = lane; i < 68; i += 32) z[i] = make_uint4(0, 0, 0, 0);
      }
      asm volatile("fence.proxy.async;" ::: "memory");
      __syncwarp();
      if (lane == 0) {
        asm volatile("red.release.gpu.global.add.u32 [%0], 1;" ::"l"(&g_zcnt[m * 32]) : "memory");
        flag_wait(&g_zcnt[m * 32], (ep + 1) * 8);
        asm volatile("fence.proxy.async;" ::: "memory");
        mbar_arrive(B_ZK);
        if (att) {
          mbar_wait(B_KD);
          asm volatile("red.release.gpu.global.add.u32 [%0], 1;" ::"l"(&g_kvcnt[j * 32]) : "memory");
          flag_wait(&g_kvcnt[j * 32], (ep + 1) * 16);
          asm volatile("fence.proxy.async;" ::: "memory");
          mbar_wait(B_SE + 8 * 16);
          const float* src = g_kv[ep & 1][j];
          mbar_expect(B_KV, 17408);
          bulk_g2s(XB, src, 16384, B_KV);
          bulk_g2s(ZS, src + 4096, 1024, B_KV);
        }
      }
    }
  } else {
    asm volatile("setmaxnreg.inc.sync.aligned.u32 240;");
    const int wg = warp >> 2;
    const uint32_t xa = wg * 512;
    const int row0 = m * 128 + warp * 16;
    TS(wg, 1);
    float ga, gb;
    float pa[32], pb[32];
    if (att) {
      uint32_t wk[4];
      load_wphi(wk, wphi, j * 8 + warp, lane);
      uint32_t kT[32], vT[32];
      float aq[64];
      {
        float acc[128];
        t1_all<true>(acc, xa, wg, ga, gb, gate_w, warp, lane);
        STEP128(8, 0, aq);
        pin(acc);
#pragma unroll
        for (int i = 0; i < 32; i++) { kT[i] = pk(acc[2 * i], acc[2 * i + 1]); vT[i] = pk(acc[64 + 2 * i], acc[64 + 2 * i + 1]); }
        pin(kT); pin(vT);
      }
#pragma unroll
      for (int i = 0; i < 4; i++) wk[i] = movm(wk[i]);
      float kv[4][4], z[8];
#pragma unroll
      for (int i = 0; i < 8; i++) z[i] = 0.f;
      k_chunk<0>(kT, vT, wk, kv, z);
      STEP128(9, 1, aq);
      k_chunk<2>(kT, vT, wk, kv, z);
      STEP128(10, 2, aq);
      k_chunk<4>(kT, vT, wk, kv, z);
      STEP128(11, 3, aq);
      k_chunk<6>(kT, vT, wk, kv, z);
      {
        unsigned ep;
        mbar_wait(B_EP);
        asm volatile("ld.shared.u32 %0, [%1];" : "=r"(ep) : "r"(EPS) : "memory");
        float* dst = g_kv[ep & 1][j];
#pragma unroll
        for (int c = 0; c < 4; c++)
          asm volatile("red.global.add.v4.f32 [%0], {%1,%2,%3,%4};" ::"l"(dst + warp * 512 + c * 128 + lane * 4), "f"(kv[c][0]), "f"(kv[c][1]), "f"(kv[c][2]), "f"(kv[c][3]) : "memory");
        const bool b4 = lane & 16, b3 = lane & 8, b2 = lane & 4;
#pragma unroll
        for (int i = 0; i < 4; i++) z[i] = (b4 ? z[4 + i] : z[i]) + __shfl_xor_sync(0xffffffffu, b4 ? z[i] : z[4 + i], 16);
#pragma unroll
        for (int i = 0; i < 2; i++) z[i] = (b3 ? z[2 + i] : z[i]) + __shfl_xor_sync(0xffffffffu, b3 ? z[i] : z[2 + i], 8);
        z[0] = (b2 ? z[1] : z[0]) + __shfl_xor_sync(0xffffffffu, b2 ? z[0] : z[1], 4);
        asm volatile("red.global.add.f32 [%0], %1;" ::"l"(dst + 4096 + warp * 32 + (lane & 3) * 8 + (lane >> 2)), "f"(z[0]) : "memory");
        __syncwarp();
        REL(B_KD);
      }
      uint32_t w0[4], w1[4];
      load_wphi(w0, wphi, j * 8, lane); load_wphi(w1, wphi, j * 8 + 1, lane);
      float a3[64];
      STEP128(12, 0, a3);
      pin(aq);
      uint32_t qa[32], phi[8][8];
#pragma unroll
      for (int i = 0; i < 32; i++) qa[i] = pk(aq[2 * i], aq[2 * i + 1]);
      pin(qa);
      q_chunk<0>(qa, w0, w1, phi);
      load_wphi(w0, wphi, j * 8 + 2, lane); load_wphi(w1, wphi, j * 8 + 3, lane);
      STEP128(13, 1, a3);
      q_chunk<2>(qa, w0, w1, phi);
      load_wphi(w0, wphi, j * 8 + 4, lane); load_wphi(w1, wphi, j * 8 + 5, lane);
      STEP128(14, 2, a3);
      q_chunk<4>(qa, w0, w1, phi);
      load_wphi(w0, wphi, j * 8 + 6, lane); load_wphi(w1, wphi, j * 8 + 7, lane);
      STEP128(15, 3, a3);
      q_chunk<6>(qa, w0, w1, phi);
      float a4[64];
      uint32_t a[64];
      STEP128(16, 0, a4);
      pin(a3);
      gu_pack<1>(a3, a, 32, 1.f - ga, 1.f - gb);
      STEP128(17, 1, a4);
      STEP128(18, 2, a4);
      mbar_wait(B_KV);
      TS(wg, 22);
      o_chunk<0, 4>(phi, a, ga, gb, lane);
      STEP128(19, 3, a4);
      o_chunk<4, 4>(phi, a, ga, gb, lane);
      __syncwarp();
      REL(B_OD);
      TS(wg, 23);
      mbar_wait(B_EF);
      issue_p2<0, 12, true, eslot_att(0)>(pa, a);
      WG_WAIT(1);
      REL(B_SE + 8 * 19);
      TS(wg, 24);
      pin(a4);
      gu_pack<1>(a4, a, 48, 1.f - ga, 1.f - gb);
      issue_p2<12, 16, false, eslot_att(0)>(pa, a);
      p2_rest<true>(pa, pb, a, &P.out, j, row0, warp, lane);
    } else {
      uint32_t a[80];
      float a2[64];
      {
        float acc[128];
        t1_all<false>(acc, xa, wg, ga, gb, gate_w, warp, lane);
        ga = 1.f - ga; gb = 1.f - gb;
        STEP128(8, 0, a2);
        pin(acc);
        gu_pack<2>(acc, a, 0, ga, gb);
      }
      STEP128(9, 1, a2);
      STEP128(10, 2, a2);
      STEP128(11, 3, a2);
      float a3[64];
      STEP128(12, 0, a3);
      pin(a2);
      gu_pack<1>(a2, a, 32, ga, gb);
      STEP128(13, 1, a3);
      STEP128(14, 2, a3);
      STEP128(15, 3, a3);
      STEP128R(16, a2);
      pin(a3);
      gu_pack<1>(a3, a, 48, ga, gb);
      STEP128(17, 1, a2);
      STEP128(18, 2, a2);
      STEP128(19, 3, a2);
      mbar_wait(B_EF);
      issue_p2<0, 16, true, eslot_ffn(0)>(pa, a);
      WG_WAIT(1);
      REL(B_SE + 8 * 19);
      TS(wg, 24);
      pin(a2);
      gu_pack<1>(a2, a, 64, ga, gb);
      issue_p2<16, 20, false, eslot_ffn(0)>(pa, a);
      p2_rest<false>(pa, pb, a, &P.out, j, row0, warp, lane);
    }
  }
}

typedef CUresult (*EncFn)(CUtensorMap*, CUtensorMapDataType, cuuint32_t, void*, const cuuint64_t*, const cuuint64_t*, const cuuint32_t*, const cuuint32_t*,
                          CUtensorMapInterleave, CUtensorMapSwizzle, CUtensorMapL2promotion, CUtensorMapFloatOOBfill);

void enc(EncFn fn, CUtensorMap* t, const void* p, int rank, const cuuint64_t* gd, const cuuint64_t* gs, const cuuint32_t* bd) {
  const cuuint32_t es[4] = {1, 1, 1, 1};
  fn(t, CU_TENSOR_MAP_DATA_TYPE_BFLOAT16, rank, const_cast<void*>(p), gd, gs, bd, es, CU_TENSOR_MAP_INTERLEAVE_NONE, CU_TENSOR_MAP_SWIZZLE_128B,
     CU_TENSOR_MAP_L2_PROMOTION_L2_256B, CU_TENSOR_MAP_FLOAT_OOB_FILL_NONE);
}
void enc2(EncFn fn, CUtensorMap* t, const void* p, int rows, int boxrows) {
  const cuuint64_t gd[2] = {512, (cuuint64_t)rows}, gs[1] = {1024};
  const cuuint32_t bd[2] = {64, (cuuint32_t)boxrows};
  enc(fn, t, p, 2, gd, gs, bd);
}

}

extern "C" void kernel_launch(void* const* d_in, const int* in_sizes, int n_in, void* d_out, int out_size) {
  void* fp = nullptr;
  cudaDriverEntryPointQueryResult qr;
  cudaGetDriverEntryPoint("cuTensorMapEncodeTiled", &fp, cudaEnableDefault, &qr);
  EncFn fn = (EncFn)fp;
  Params P;
  enc2(fn, &P.x, d_in[0], 2048, 128);
  {
    const cuuint64_t gd[4] = {64, 512, 8, 3}, gs[3] = {3072, 128, 1024};
    const cuuint32_t b1[4] = {64, 64, 2, 2}, b2[4] = {64, 128, 2, 1};
    enc(fn, &P.kv, d_in[1], 4, gd, gs, b1);
    enc(fn, &P.q, d_in[1], 4, gd, gs, b2);
  }
  {
    const cuuint64_t gd[3] = {64, 512, 28}, gs[2] = {3584, 128};
    const cuuint32_t b1[3] = {64, 64, 2}, b2[3] = {64, 128, 1};
    enc(fn, &P.g1, d_in[5], 3, gd, gs, b1); enc(fn, &P.u1, d_in[6], 3, gd, gs, b1);
    enc(fn, &P.g2, d_in[5], 3, gd, gs, b2); enc(fn, &P.u2, d_in[6], 3, gd, gs, b2);
  }
  enc2(fn, &P.wo, d_in[3], 512, 128);
  enc2(fn, &P.wda, d_in[7], 1792, 128);
  enc2(fn, &P.wdf, d_in[7], 1792, 160);
  enc2(fn, &P.out, d_out, 2048, 16);
  cudaFuncSetAttribute(fused_kernel, cudaFuncAttributeMaxDynamicSharedMemorySize, SMEM_BYTES);
  fused_kernel<<<128, NTHREADS, SMEM_BYTES>>>(P, (const __nv_bfloat16*)d_in[2], (const __nv_bfloat16*)d_in[8], (__nv_bfloat16*)d_out);
}
```

```cpp
#include <cuda_runtime.h>
#include <cuda.h>
#include <cuda_bf16.h>
#include <stdint.h>
#include <type_traits>

template <uint32_t AI, uint32_t BI, uint32_t BH = 0x40000040> __device__ __forceinline__ void wg_ss256_t01_z(float (&d)[128], uint32_t ab, uint32_t bb) {
  asm volatile("{\n.reg .pred p;\n.reg .b32 t, u;\n.reg .b64 da, db;\nsetp.ne.b32 p, 0, 0;\nadd.u32 t, %128, %130;\nadd.u32 u, %129, %131;\n"
    "mov.b64 da, {t, 0x40000040};\nmov.b64 db, {u, %132};\n"
    "wgmma.mma_async.sync.aligned.m64n256k16.f32.bf16.bf16 "
    "{%0, %1, %2, %3, %4, %5, %6, %7, %8, %9, %10, %11, %12, %13, %14, %15, %16, %17, %18, %19, %20, %21, %22, %23, %24, %25, %26, %27, %28, %29, %30, %31, %32, %33, %34, %35, %36, %37, %38, %39, %40, %41, %42, %43, %44, %45, %46, %47, %48, %49, %50, %51, %52, %53, %54, %55, %56, %57, %58, %59, %60, %61, %62, %63, %64, %65, %66, %67, %68, %69, %70, %71, %72, %73, %74, %75, %76, %77, %78, %79, %80, %81, %82, %83, %84, %85, %86, %87, %88, %89, %90, %91, %92, %93, %94, %95, %96, %97, %98, %99, %100, %101, %102, %103, %104, %105, %106, %107, %108, %109, %110, %111, %112, %113, %114, %115, %116, %117, %118, %119, %120, %121, %122, %123, %124, %125, %126, %127}, da, db, p, 1, 1, 0, 1;\n}\n"
    : "=f"(d[0]), "=f"(d[1]), "=f"(d[2]), "=f"(d[3]), "=f"(d[4]), "=f"(d[5]), "=f"(d[6]), "=f"(d[7]), "=f"(d[8]), "=f"(d[9]), "=f"(d[10]), "=f"(d[11]), "=f"(d[12]), "=f"(d[13]), "=f"(d[14]), "=f"(d[15]), "=f"(d[16]), "=f"(d[17]), "=f"(d[18]), "=f"(d[19]), "=f"(d[20]), "=f"(d[21]), "=f"(d[22]), "=f"(d[23]), "=f"(d[24]), "=f"(d[25]), "=f"(d[26]), "=f"(d[27]), "=f"(d[28]), "=f"(d[29]), "=f"(d[30]), "=f"(d[31]), "=f"(d[32]), "=f"(d[33]), "=f"(d[34]), "=f"(d[35]), "=f"(d[36]), "=f"(d[37]), "=f"(d[38]), "=f"(d[39]), "=f"(d[40]), "=f"(d[41]), "=f"(d[42]), "=f"(d[43]), "=f"(d[44]), "=f"(d[45]), "=f"(d[46]), "=f"(d[47]), "=f"(d[48]), "=f"(d[49]), "=f"(d[50]), "=f"(d[51]), "=f"(d[52]), "=f"(d[53]), "=f"(d[54]), "=f"(d[55]), "=f"(d[56]), "=f"(d[57]), "=f"(d[58]), "=f"(d[59]), "=f"(d[60]), "=f"(d[61]), "=f"(d[62]), "=f"(d[63]), "=f"(d[64]), "=f"(d[65]), "=f"(d[66]), "=f"(d[67]), "=f"(d[68]), "=f"(d[69]), "=f"(d[70]), "=f"(d[71]), "=f"(d[72]), "=f"(d[73]), "=f"(d[74]), "=f"(d[75]), "=f"(d[76]), "=f"(d[77]), "=f"(d[78]), "=f"(d[79]), "=f"(d[80]), "=f"(d[81]), "=f"(d[82]), "=f"(d[83]), "=f"(d[84]), "=f"(d[85]), "=f"(d[86]), "=f"(d[87]), "=f"(d[88]), "=f"(d[89]), "=f"(d[90]), "=f"(d[91]), "=f"(d[92]), "=f"(d[93]), "=f"(d[94]), "=f"(d[95]), "=f"(d[96]), "=f"(d[97]), "=f"(d[98]), "=f"(d[99]), "=f"(d[100]), "=f"(d[101]), "=f"(d[102]), "=f"(d[103]), "=f"(d[104]), "=f"(d[105]), "=f"(d[106]), "=f"(d[107]), "=f"(d[108]), "=f"(d[109]), "=f"(d[110]), "=f"(d[111]), "=f"(d[112]), "=f"(d[113]), "=f"(d[114]), "=f"(d[115]), "=f"(d[116]), "=f"(d[117]), "=f"(d[118]), "=f"(d[119]), "=f"(d[120]), "=f"(d[121]), "=f"(d[122]), "=f"(d[123]), "=f"(d[124]), "=f"(d[125]), "=f"(d[126]), "=f"(d[127])
    : "r"(ab), "r"(bb), "n"(AI), "n"(BI), "n"(BH));
}
template <uint32_t AI, uint32_t BI, uint32_t BH = 0x40000040> __device__ __forceinline__ void wg_ss256_t01_a(float (&d)[128], uint32_t ab, uint32_t bb) {
  asm volatile("{\n.reg .pred p;\n.reg .b32 t, u;\n.reg .b64 da, db;\nsetp.ne.b32 p, 1, 0;\nadd.u32 t, %128, %130;\nadd.u32 u, %129, %131;\n"
    "mov.b64 da, {t, 0x40000040};\nmov.b64 db, {u, %132};\n"
    "wgmma.mma_async.sync.aligned.m64n256k16.f32.bf16.bf16 "
    "{%0, %1, %2, %3, %4, %5, %6, %7, %8, %9, %10, %11, %12, %13, %14, %15, %16, %17, %18, %19, %20, %21, %22, %23, %24, %25, %26, %27, %28, %29, %30, %31, %32, %33, %34, %35, %36, %37, %38, %39, %40, %41, %42, %43, %44, %45, %46, %47, %48, %49, %50, %51, %52, %53, %54, %55, %56, %57, %58, %59, %60, %61, %62, %63, %64, %65, %66, %67, %68, %69, %70, %71, %72, %73, %74, %75, %76, %77, %78, %79, %80, %81, %82, %83, %84, %85, %86, %87, %88, %89, %90, %91, %92, %93, %94, %95, %96, %97, %98, %99, %100, %101, %102, %103, %104, %105, %106, %107, %108, %109, %110, %111, %112, %113, %114, %115, %116, %117, %118, %119, %120, %121, %122, %123, %124, %125, %126, %127}, da, db, p, 1, 1, 0, 1;\n}\n"
    : "+f"(d[0]), "+f"(d[1]), "+f"(d[2]), "+f"(d[3]), "+f"(d[4]), "+f"(d[5]), "+f"(d[6]), "+f"(d[7]), "+f"(d[8]), "+f"(d[9]), "+f"(d[10]), "+f"(d[11]), "+f"(d[12]), "+f"(d[13]), "+f"(d[14]), "+f"(d[15]), "+f"(d[16]), "+f"(d[17]), "+f"(d[18]), "+f"(d[19]), "+f"(d[20]), "+f"(d[21]), "+f"(d[22]), "+f"(d[23]), "+f"(d[24]), "+f"(d[25]), "+f"(d[26]), "+f"(d[27]), "+f"(d[28]), "+f"(d[29]), "+f"(d[30]), "+f"(d[31]), "+f"(d[32]), "+f"(d[33]), "+f"(d[34]), "+f"(d[35]), "+f"(d[36]), "+f"(d[37]), "+f"(d[38]), "+f"(d[39]), "+f"(d[40]), "+f"(d[41]), "+f"(d[42]), "+f"(d[43]), "+f"(d[44]), "+f"(d[45]), "+f"(d[46]), "+f"(d[47]), "+f"(d[48]), "+f"(d[49]), "+f"(d[50]), "+f"(d[51]), "+f"(d[52]), "+f"(d[53]), "+f"(d[54]), "+f"(d[55]), "+f"(d[56]), "+f"(d[57]), "+f"(d[58]), "+f"(d[59]), "+f"(d[60]), "+f"(d[61]), "+f"(d[62]), "+f"(d[63]), "+f"(d[64]), "+f"(d[65]), "+f"(d[66]), "+f"(d[67]), "+f"(d[68]), "+f"(d[69]), "+f"(d[70]), "+f"(d[71]), "+f"(d[72]), "+f"(d[73]), "+f"(d[74]), "+f"(d[75]), "+f"(d[76]), "+f"(d[77]), "+f"(d[78]), "+f"(d[79]), "+f"(d[80]), "+f"(d[81]), "+f"(d[82]), "+f"(d[83]), "+f"(d[84]), "+f"(d[85]), "+f"(d[86]), "+f"(d[87]), "+f"(d[88]), "+f"(d[89]), "+f"(d[90]), "+f"(d[91]), "+f"(d[92]), "+f"(d[93]), "+f"(d[94]), "+f"(d[95]), "+f"(d[96]), "+f"(d[97]), "+f"(d[98]), "+f"(d[99]), "+f"(d[100]), "+f"(d[101]), "+f"(d[102]), "+f"(d[103]), "+f"(d[104]), "+f"(d[105]), "+f"(d[106]), "+f"(d[107]), "+f"(d[108]), "+f"(d[109]), "+f"(d[110]), "+f"(d[111]), "+f"(d[112]), "+f"(d[113]), "+f"(d[114]), "+f"(d[115]), "+f"(d[116]), "+f"(d[117]), "+f"(d[118]), "+f"(d[119]), "+f"(d[120]), "+f"(d[121]), "+f"(d[122]), "+f"(d[123]), "+f"(d[124]), "+f"(d[125]), "+f"(d[126]), "+f"(d[127])
    : "r"(ab), "r"(bb), "n"(AI), "n"(BI), "n"(BH));
}
template <uint32_t AI, uint32_t BI, uint32_t BH = 0x40000040> __device__ __forceinline__ void wg_ss128_t01_a(float (&d)[64], uint32_t ab, uint32_t bb) {
  asm volatile("{\n.reg .pred p;\n.reg .b32 t, u;\n.reg .b64 da, db;\nsetp.ne.b32 p, 1, 0;\nadd.u32 t, %64, %66;\nadd.u32 u, %65, %67;\n"
    "mov.b64 da, {t, 0x40000040};\nmov.b64 db, {u, %68};\n"
    "wgmma.mma_async.sync.aligned.m64n128k16.f32.bf16.bf16 "
    "{%0, %1, %2, %3, %4, %5, %6, %7, %8, %9, %10, %11, %12, %13, %14, %15, %16, %17, %18, %19, %20, %21, %22, %23, %24, %25, %26, %27, %28, %29, %30, %31, %32, %33, %34, %35, %36, %37, %38, %39, %40, %41, %42, %43, %44, %45, %46, %47, %48, %49, %50, %51, %52, %53, %54, %55, %56, %57, %58, %59, %60, %61, %62, %63}, da, db, p, 1, 1, 0, 1;\n}\n"
    : "+f"(d[0]), "+f"(d[1]), "+f"(d[2]), "+f"(d[3]), "+f"(d[4]), "+f"(d[5]), "+f"(d[6]), "+f"(d[7]), "+f"(d[8]), "+f"(d[9]), "+f"(d[10]), "+f"(d[11]), "+f"(d[12]), "+f"(d[13]), "+f"(d[14]), "+f"(d[15]), "+f"(d[16]), "+f"(d[17]), "+f"(d[18]), "+f"(d[19]), "+f"(d[20]), "+f"(d[21]), "+f"(d[22]), "+f"(d[23]), "+f"(d[24]), "+f"(d[25]), "+f"(d[26]), "+f"(d[27]), "+f"(d[28]), "+f"(d[29]), "+f"(d[30]), "+f"(d[31]), "+f"(d[32]), "+f"(d[33]), "+f"(d[34]), "+f"(d[35]), "+f"(d[36]), "+f"(d[37]), "+f"(d[38]), "+f"(d[39]), "+f"(d[40]), "+f"(d[41]), "+f"(d[42]), "+f"(d[43]), "+f"(d[44]), "+f"(d[45]), "+f"(d[46]), "+f"(d[47]), "+f"(d[48]), "+f"(d[49]), "+f"(d[50]), "+f"(d[51]), "+f"(d[52]), "+f"(d[53]), "+f"(d[54]), "+f"(d[55]), "+f"(d[56]), "+f"(d[57]), "+f"(d[58]), "+f"(d[59]), "+f"(d[60]), "+f"(d[61]), "+f"(d[62]), "+f"(d[63])
    : "r"(ab), "r"(bb), "n"(AI), "n"(BI), "n"(BH));
}
template <uint32_t AI, uint32_t BI, uint32_t BH = 0x40000040> __device__ __forceinline__ void wg_ss128_t01_p(float (&d)[64], uint32_t ab, uint32_t bb, uint32_t sd) {
  asm volatile("{\n.reg .pred p;\n.reg .b32 t, u;\n.reg .b64 da, db;\nsetp.ne.b32 p, %69, 0;\nadd.u32 t, %64, %66;\nadd.u32 u, %65, %67;\n"
    "mov.b64 da, {t, 0x40000040};\nmov.b64 db, {u, %68};\n"
    "wgmma.mma_async.sync.aligned.m64n128k16.f32.bf16.bf16 "
    "{%0, %1, %2, %3, %4, %5, %6, %7, %8, %9, %10, %11, %12, %13, %14, %15, %16, %17, %18, %19, %20, %21, %22, %23, %24, %25, %26, %27, %28, %29, %30, %31, %32, %33, %34, %35, %36, %37, %38, %39, %40, %41, %42, %43, %44, %45, %46, %47, %48, %49, %50, %51, %52, %53, %54, %55, %56, %57, %58, %59, %60, %61, %62, %63}, da, db, p, 1, 1, 0, 1;\n}\n"
    : "+f"(d[0]), "+f"(d[1]), "+f"(d[2]), "+f"(d[3]), "+f"(d[4]), "+f"(d[5]), "+f"(d[6]), "+f"(d[7]), "+f"(d[8]), "+f"(d[9]), "+f"(d[10]), "+f"(d[11]), "+f"(d[12]), "+f"(d[13]), "+f"(d[14]), "+f"(d[15]), "+f"(d[16]), "+f"(d[17]), "+f"(d[18]), "+f"(d[19]), "+f"(d[20]), "+f"(d[21]), "+f"(d[22]), "+f"(d[23]), "+f"(d[24]), "+f"(d[25]), "+f"(d[26]), "+f"(d[27]), "+f"(d[28]), "+f"(d[29]), "+f"(d[30]), "+f"(d[31]), "+f"(d[32]), "+f"(d[33]), "+f"(d[34]), "+f"(d[35]), "+f"(d[36]), "+f"(d[37]), "+f"(d[38]), "+f"(d[39]), "+f"(d[40]), "+f"(d[41]), "+f"(d[42]), "+f"(d[43]), "+f"(d[44]), "+f"(d[45]), "+f"(d[46]), "+f"(d[47]), "+f"(d[48]), "+f"(d[49]), "+f"(d[50]), "+f"(d[51]), "+f"(d[52]), "+f"(d[53]), "+f"(d[54]), "+f"(d[55]), "+f"(d[56]), "+f"(d[57]), "+f"(d[58]), "+f"(d[59]), "+f"(d[60]), "+f"(d[61]), "+f"(d[62]), "+f"(d[63])
    : "r"(ab), "r"(bb), "n"(AI), "n"(BI), "n"(BH), "r"(sd));
}
template <uint32_t BI> __device__ __forceinline__ void wg_rs16_z(float (&d)[8], uint32_t a0, uint32_t a1, uint32_t a2, uint32_t a3, uint32_t bb) {
  asm volatile("{\n.reg .pred p;\n.reg .b32 u;\n.reg .b64 db;\nsetp.ne.b32 p, 0, 0;\nadd.u32 u, %12, %13;\nmov.b64 db, {u, 0xC0000010};\n"
    "wgmma.mma_async.sync.aligned.m64n16k16.f32.bf16.bf16 "
    "{%0, %1, %2, %3, %4, %5, %6, %7}, {%8, %9, %10, %11}, db, p, 1, 1, 1;\n}\n"
    : "=f"(d[0]), "=f"(d[1]), "=f"(d[2]), "=f"(d[3]), "=f"(d[4]), "=f"(d[5]), "=f"(d[6]), "=f"(d[7])
    : "r"(a0), "r"(a1), "r"(a2), "r"(a3), "r"(bb), "n"(BI));
}
template <uint32_t BI> __device__ __forceinline__ void wg_rs24_z(float (&d)[12], uint32_t a0, uint32_t a1, uint32_t a2, uint32_t a3, uint32_t bb) {
  asm volatile("{\n.reg .pred p;\n.reg .b32 u;\n.reg .b64 db;\nsetp.ne.b32 p, 0, 0;\nadd.u32 u, %16, %17;\nmov.b64 db, {u, 0x00000010};\n"
    "wgmma.mma_async.sync.aligned.m64n24k16.f32.bf16.bf16 "
    "{%0, %1, %2, %3, %4, %5, %6, %7, %8, %9, %10, %11}, {%12, %13, %14, %15}, db, p, 1, 1, 1;\n}\n"
    : "=f"(d[0]), "=f"(d[1]), "=f"(d[2]), "=f"(d[3]), "=f"(d[4]), "=f"(d[5]), "=f"(d[6]), "=f"(d[7]), "=f"(d[8]), "=f"(d[9]), "=f"(d[10]), "=f"(d[11])
    : "r"(a0), "r"(a1), "r"(a2), "r"(a3), "r"(bb), "n"(BI));
}
template <uint32_t AI, uint32_t BI, uint32_t BH = 0x40000040> __device__ __forceinline__ void wg_ss40_t11_z(float (&d)[20], uint32_t ab, uint32_t bb) {
  asm volatile("{\n.reg .pred p;\n.reg .b32 t, u;\n.reg .b64 da, db;\nsetp.ne.b32 p, 0, 0;\nadd.u32 t, %20, %22;\nadd.u32 u, %21, %23;\n"
    "mov.b64 da, {t, 0x40000040};\nmov.b64 db, {u, %24};\n"
    "wgmma.mma_async.sync.aligned.m64n40k16.f32.bf16.bf16 "
    "{%0, %1, %2, %3, %4, %5, %6, %7, %8, %9, %10, %11, %12, %13, %14, %15, %16, %17, %18, %19}, da, db, p, 1, 1, 1, 1;\n}\n"
    : "=f"(d[0]), "=f"(d[1]), "=f"(d[2]), "=f"(d[3]), "=f"(d[4]), "=f"(d[5]), "=f"(d[6]), "=f"(d[7]), "=f"(d[8]), "=f"(d[9]), "=f"(d[10]), "=f"(d[11]), "=f"(d[12]), "=f"(d[13]), "=f"(d[14]), "=f"(d[15]), "=f"(d[16]), "=f"(d[17]), "=f"(d[18]), "=f"(d[19])
    : "r"(ab), "r"(bb), "n"(AI), "n"(BI), "n"(BH));
}
template <uint32_t AI, uint32_t BI, uint32_t BH = 0x40000040> __device__ __forceinline__ void wg_ss40_t11_a(float (&d)[20], uint32_t ab, uint32_t bb) {
  asm volatile("{\n.reg .pred p;\n.reg .b32 t, u;\n.reg .b64 da, db;\nsetp.ne.b32 p, 1, 0;\nadd.u32 t, %20, %22;\nadd.u32 u, %21, %23;\n"
    "mov.b64 da, {t, 0x40000040};\nmov.b64 db, {u, %24};\n"
    "wgmma.mma_async.sync.aligned.m64n40k16.f32.bf16.bf16 "
    "{%0, %1, %2, %3, %4, %5, %6, %7, %8, %9, %10, %11, %12, %13, %14, %15, %16, %17, %18, %19}, da, db, p, 1, 1, 1, 1;\n}\n"
    : "+f"(d[0]), "+f"(d[1]), "+f"(d[2]), "+f"(d[3]), "+f"(d[4]), "+f"(d[5]), "+f"(d[6]), "+f"(d[7]), "+f"(d[8]), "+f"(d[9]), "+f"(d[10]), "+f"(d[11]), "+f"(d[12]), "+f"(d[13]), "+f"(d[14]), "+f"(d[15]), "+f"(d[16]), "+f"(d[17]), "+f"(d[18]), "+f"(d[19])
    : "r"(ab), "r"(bb), "n"(AI), "n"(BI), "n"(BH));
}
template <uint32_t BI> __device__ __forceinline__ void wg_rs64_z(float (&d)[32], uint32_t a0, uint32_t a1, uint32_t a2, uint32_t a3, uint32_t bb) {
  asm volatile("{\n.reg .pred p;\n.reg .b32 u;\n.reg .b64 db;\nsetp.ne.b32 p, 0, 0;\nadd.u32 u, %36, %37;\nmov.b64 db, {u, 0x40000040};\n"
    "wgmma.mma_async.sync.aligned.m64n64k16.f32.bf16.bf16 "
    "{%0, %1, %2, %3, %4, %5, %6, %7, %8, %9, %10, %11, %12, %13, %14, %15, %16, %17, %18, %19, %20, %21, %22, %23, %24, %25, %26, %27, %28, %29, %30, %31}, {%32, %33, %34, %35}, db, p, 1, 1, 1;\n}\n"
    : "=f"(d[0]), "=f"(d[1]), "=f"(d[2]), "=f"(d[3]), "=f"(d[4]), "=f"(d[5]), "=f"(d[6]), "=f"(d[7]), "=f"(d[8]), "=f"(d[9]), "=f"(d[10]), "=f"(d[11]), "=f"(d[12]), "=f"(d[13]), "=f"(d[14]), "=f"(d[15]), "=f"(d[16]), "=f"(d[17]), "=f"(d[18]), "=f"(d[19]), "=f"(d[20]), "=f"(d[21]), "=f"(d[22]), "=f"(d[23]), "=f"(d[24]), "=f"(d[25]), "=f"(d[26]), "=f"(d[27]), "=f"(d[28]), "=f"(d[29]), "=f"(d[30]), "=f"(d[31])
    : "r"(a0), "r"(a1), "r"(a2), "r"(a3), "r"(bb), "n"(BI));
}
template <uint32_t BI> __device__ __forceinline__ void wg_rs64_a(float (&d)[32], uint32_t a0, uint32_t a1, uint32_t a2, uint32_t a3, uint32_t bb) {
  asm volatile("{\n.reg .pred p;\n.reg .b32 u;\n.reg .b64 db;\nsetp.ne.b32 p, 1, 0;\nadd.u32 u, %36, %37;\nmov.b64 db, {u, 0x40000040};\n"
    "wgmma.mma_async.sync.aligned.m64n64k16.f32.bf16.bf16 "
    "{%0, %1, %2, %3, %4, %5, %6, %7, %8, %9, %10, %11, %12, %13, %14, %15, %16, %17, %18, %19, %20, %21, %22, %23, %24, %25, %26, %27, %28, %29, %30, %31}, {%32, %33, %34, %35}, db, p, 1, 1, 1;\n}\n"
    : "+f"(d[0]), "+f"(d[1]), "+f"(d[2]), "+f"(d[3]), "+f"(d[4]), "+f"(d[5]), "+f"(d[6]), "+f"(d[7]), "+f"(d[8]), "+f"(d[9]), "+f"(d[10]), "+f"(d[11]), "+f"(d[12]), "+f"(d[13]), "+f"(d[14]), "+f"(d[15]), "+f"(d[16]), "+f"(d[17]), "+f"(d[18]), "+f"(d[19]), "+f"(d[20]), "+f"(d[21]), "+f"(d[22]), "+f"(d[23]), "+f"(d[24]), "+f"(d[25]), "+f"(d[26]), "+f"(d[27]), "+f"(d[28]), "+f"(d[29]), "+f"(d[30]), "+f"(d[31])
    : "r"(a0), "r"(a1), "r"(a2), "r"(a3), "r"(bb), "n"(BI));
}

namespace {

constexpr uint32_t SB = 1024;
constexpr uint32_t XB = SB;
constexpr uint32_t RB = SB + 131072;
constexpr uint32_t MISC = RB + 98304;
constexpr uint32_t WP = MISC;
constexpr uint32_t GV = MISC + 2048;
constexpr uint32_t GW = GV;
constexpr uint32_t BAR = MISC + 2304;
constexpr uint32_t B_XF = BAR;
constexpr uint32_t B_F = BAR + 8 * 8;
constexpr uint32_t B_KV = BAR + 36 * 8;
constexpr uint32_t B_ZK = BAR + 37 * 8;
constexpr uint32_t B_G = BAR + 38 * 8;
constexpr uint32_t B_EP = BAR + 39 * 8;
constexpr uint32_t B_E = BAR + 41 * 8;
constexpr uint32_t KI = XB + 65536;
constexpr uint32_t B_GX = BAR + 69 * 8;
constexpr uint32_t B_KD = BAR + 70 * 8;
constexpr uint32_t B_KI = BAR + 71 * 8;
constexpr uint32_t EPS = BAR + 72 * 8;
constexpr int SMEM_BYTES = 131072 + 98304 + 3072;
constexpr int NTHREADS = 384;
constexpr uint32_t ETBL = 0x1B280012u;
constexpr uint32_t STG = SB + 36864;

enum { M_X, M_KV, M_Q, M_GU1, M_GU2, M_WO, M_WD, M_OUT, M_WP, M_N };
struct Params { CUtensorMap t[M_N]; const char* pf[2]; };

__device__ float g_kv[2][8][2176];
__device__ float g_gate[16][8][128];
__device__ unsigned g_kvcnt[8 * 32];
__device__ unsigned g_zcnt[16 * 32];
#define TS(w, i) do {} while (0)
#define TS2(i) do {} while (0)

__device__ __forceinline__ void mbar_init(uint32_t bar, int cnt) { asm volatile("mbarrier.init.shared::cta.b64 [%0], %1;" ::"r"(bar), "r"(cnt)); }
__device__ __forceinline__ void mbar_expect(uint32_t bar, uint32_t bytes) {
  asm volatile("mbarrier.arrive.expect_tx.shared::cta.b64 _, [%0], %1;" ::"r"(bar), "r"(bytes) : "memory");
}
__device__ __forceinline__ void mbar_arrive(uint32_t bar) { asm volatile("mbarrier.arrive.shared::cta.b64 _, [%0];" ::"r"(bar) : "memory"); }
__device__ __forceinline__ void mbar_wait(uint32_t bar) {
  asm volatile(
      "{\n.reg .pred p;\n.reg .u32 c;\nmov.u32 c, 0;\n"
      "LW%=:\nmbarrier.try_wait.parity.shared::cta.b64 p, [%0], 0;\n@p bra LD%=;\n"
      "add.u32 c, c, 1;\nsetp.lt.u32 p, c, 2097152;\n@p bra LW%=;\ntrap;\nLD%=:\n}" ::"r"(bar) : "memory");
}
__device__ __forceinline__ void flag_wait(const unsigned* p, unsigned target) {
  asm volatile(
      "{\n.reg .pred p;\n.reg .u32 c, v;\nmov.u32 c, 0;\n"
      "LW%=:\nld.acquire.gpu.global.u32 v, [%0];\nsub.u32 v, v, %1;\nsetp.ge.s32 p, v, 0;\n@p bra LD%=;\n"
      "add.u32 c, c, 1;\nsetp.lt.u32 p, c, 2097152;\n@p bra LW%=;\ntrap;\nLD%=:\n}" ::"l"(p), "r"(target) : "memory");
}
__device__ __forceinline__ void tma3(uint32_t dst, const CUtensorMap* m, uint32_t bar, int c0, int c1, int c2) {
  asm volatile("cp.async.bulk.tensor.3d.shared::cluster.global.mbarrier::complete_tx::bytes [%0], [%1, {%3,%4,%5}], [%2];" ::"r"(dst), "l"(m), "r"(bar), "r"(c0), "r"(c1), "r"(c2) : "memory");
}
__device__ __forceinline__ void tma4(uint32_t dst, const CUtensorMap* m, uint32_t bar, int c0, int c1) {
  asm volatile("cp.async.bulk.tensor.4d.shared::cluster.global.mbarrier::complete_tx::bytes [%0], [%1, {%3,%4,%5,%5}], [%2];" ::"r"(dst), "l"(m), "r"(bar), "r"(c0), "r"(c1), "r"(0) : "memory");
}
__device__ __forceinline__ void tma2(uint32_t dst, const CUtensorMap* m, uint32_t bar, int c0, int c1) {
  asm volatile("cp.async.bulk.tensor.2d.shared::cluster.global.mbarrier::complete_tx::bytes [%0], [%1, {%3,%4}], [%2];" ::"r"(dst), "l"(m), "r"(bar), "r"(c0), "r"(c1) : "memory");
}
__device__ __forceinline__ void pf3(const CUtensorMap* m, int c0, int c1, int c2) {
  asm volatile("cp.async.bulk.prefetch.tensor.3d.L2.global [%0, {%1,%2,%3}];" ::"l"(m), "r"(c0), "r"(c1), "r"(c2) : "memory");
}
__device__ __forceinline__ void pf4(const CUtensorMap* m, int c0, int c1) {
  asm volatile("cp.async.bulk.prefetch.tensor.4d.L2.global [%0, {%1,%2,%3,%3}];" ::"l"(m), "r"(c0), "r"(c1), "r"(0) : "memory");
}
__device__ __forceinline__ void pf_lin(const char* p, uint32_t sz) { asm volatile("cp.async.bulk.prefetch.L2.global [%0], %1;" ::"l"(p), "r"(sz) : "memory"); }
__device__ __forceinline__ void prefetch_tm(const CUtensorMap* m) { asm volatile("prefetch.tensormap [%0];" ::"l"(m) : "memory"); }
__host__ __device__ constexpr uint32_t dlo(uint32_t addr, uint32_t lbo) { return ((addr & 0x3FFFF) >> 4) | ((lbo >> 4) << 16); }
template <int I, int N, class F> __device__ __forceinline__ void sfor(F&& f) {
  if constexpr (I < N) { f(std::integral_constant<int, I>{}); sfor<I + 1, N>(f); }
}
#define WG_FENCE() asm volatile("wgmma.fence.sync.aligned;" ::: "memory")
#define WG_COMMIT() asm volatile("wgmma.commit_group.sync.aligned;" ::: "memory")
#define WG_WAIT(n) asm volatile("wgmma.wait_group.sync.aligned %0;" ::"n"(n) : "memory")
template <int N> __device__ __forceinline__ void pin(float (&a)[N]) {
#pragma unroll
  for (int i = 0; i < N; i++) asm volatile("" : "+f"(a[i])::"memory");
}
template <int N> __device__ __forceinline__ void pin(uint32_t (&a)[N]) {
#pragma unroll
  for (int i = 0; i < N; i++) asm volatile("" : "+r"(a[i])::"memory");
}
__device__ __forceinline__ uint32_t pk(float lo, float hi) { uint32_t r; asm("cvt.rn.bf16x2.f32 %0, %1, %2;" : "=r"(r) : "f"(hi), "f"(lo)); return r; }
__device__ __forceinline__ float blo(uint32_t v) { return __uint_as_float(v << 16); }
__device__ __forceinline__ float bhi(uint32_t v) { return __uint_as_float(v & 0xffff0000u); }
__device__ __forceinline__ float ex2(float x) { float y; asm("ex2.approx.ftz.f32 %0, %1;" : "=f"(y) : "f"(x)); return y; }
__device__ __forceinline__ float rcp(float x) { float y; asm("rcp.approx.ftz.f32 %0, %1;" : "=f"(y) : "f"(x)); return y; }
__device__ __forceinline__ uint4 lds128(uint32_t a) { uint4 v; asm volatile("ld.shared.v4.u32 {%0,%1,%2,%3}, [%4];" : "=r"(v.x), "=r"(v.y), "=r"(v.z), "=r"(v.w) : "r"(a) : "memory"); return v; }
__device__ __forceinline__ uint32_t lds32(uint32_t a) { uint32_t v; asm volatile("ld.shared.u32 %0, [%1];" : "=r"(v) : "r"(a) : "memory"); return v; }
__device__ __forceinline__ float lds_bf(uint32_t a) { uint32_t v; asm volatile("ld.shared.u16 %0, [%1];" : "=r"(v) : "r"(a) : "memory"); return __uint_as_float(v << 16); }
__device__ __forceinline__ void sts128(uint32_t a, uint32_t x) { asm volatile("st.shared.v4.u32 [%0], {%1,%1,%1,%1};" ::"r"(a), "r"(x) : "memory"); }
__device__ __forceinline__ void sts32(uint32_t a, uint32_t v) { asm volatile("st.shared.u32 [%0], %1;" ::"r"(a), "r"(v) : "memory"); }
__device__ __forceinline__ float4 ldg_l2(const float* p) {
  float4 v; asm volatile("ld.relaxed.gpu.global.v4.f32 {%0,%1,%2,%3}, [%4];" : "=f"(v.x), "=f"(v.y), "=f"(v.z), "=f"(v.w) : "l"(p) : "memory"); return v;
}
__device__ __forceinline__ void stsm4(uint32_t a, uint32_t r0, uint32_t r1, uint32_t r2, uint32_t r3) {
  asm volatile("stmatrix.sync.aligned.m8n8.x4.shared.b16 [%0], {%1,%2,%3,%4};" ::"r"(a), "r"(r0), "r"(r1), "r"(r2), "r"(r3) : "memory");
}
__device__ __forceinline__ float dot8(uint4 x, uint4 w, float acc) {
  acc = fmaf(blo(x.x), blo(w.x), acc); acc = fmaf(bhi(x.x), bhi(w.x), acc);
  acc = fmaf(blo(x.y), blo(w.y), acc); acc = fmaf(bhi(x.y), bhi(w.y), acc);
  acc = fmaf(blo(x.z), blo(w.z), acc); acc = fmaf(bhi(x.z), bhi(w.z), acc);
  acc = fmaf(blo(x.w), blo(w.w), acc); acc = fmaf(bhi(x.w), bhi(w.w), acc);
  return acc;
}

constexpr float LOG2E = 1.4426950408889634f;
template <int T0, int T1>
__device__ __forceinline__ void row_max(const float (&c)[4][8], float (&mx)[4][4]) {
#pragma unroll
  for (int i = 2 * T0; i < 2 * T1; i++) {
    const int t = i >> 1, r = i & 1;
    mx[t][r] = fmaxf(fmaxf(c[t][2 * r], c[t][2 * r + 1]), fmaxf(c[t][4 + 2 * r], c[t][5 + 2 * r]));
    mx[t][2 + r] = fminf(fminf(c[t][2 * r], c[t][2 * r + 1]), fminf(c[t][4 + 2 * r], c[t][5 + 2 * r]));
  }
#pragma unroll
  for (int m = 1; m <= 2; m++)
#pragma unroll
    for (int i = 4 * T0; i < 4 * T1; i++) {
      const float o = __shfl_xor_sync(0xffffffffu, mx[i >> 2][i & 3], m);
      mx[i >> 2][i & 3] = (i & 2) ? fminf(mx[i >> 2][i & 3], o) : fmaxf(mx[i >> 2][i & 3], o);
    }
#pragma unroll
  for (int i = 4 * T0; i < 4 * T1; i++) mx[i >> 2][i & 3] *= (i & 2) ? LOG2E : -LOG2E;
}
__device__ __forceinline__ void row_exp(const float (&c)[8], const float (&mx)[4], float (&e)[16]) {
#pragma unroll
  for (int i = 0; i < 8; i++) { e[i] = ex2(fmaf(c[i], LOG2E, mx[(i >> 1) & 1])); e[8 + i] = ex2(fmaf(c[i], -LOG2E, mx[2 + ((i >> 1) & 1)])); }
}
__device__ __forceinline__ uint32_t hmul2(uint32_t a, uint32_t b) { uint32_t d; asm("mul.rn.bf16x2 %0, %1, %2;" : "=r"(d) : "r"(a), "r"(b)); return d; }

template <int G0, int U0, int OFF, int CNT, int N, int M>
__device__ __forceinline__ void gu_pack(const float (&a)[N], uint32_t (&h)[M], float sa, float sb) {
  const uint32_t s[2] = {pk(sa, sa), pk(sb, sb)};
#pragma unroll
  for (int i = 0; i < CNT; i++) h[OFF + i] = hmul2(pk(a[G0 + 2 * i] * a[U0 + 2 * i], a[G0 + 2 * i + 1] * a[U0 + 2 * i + 1]), s[i & 1]);
#pragma unroll
  for (int i = 0; i < CNT; i++) asm volatile("" : "+r"(h[OFF + i])::"memory");
}

#define REL(bar) do { if (lane == 0) mbar_arrive(bar); } while (0)

template <int W, int K0, int K1, int MODE = 0>
__device__ __forceinline__ void hg256(float (&acc)[128], uint32_t xd, uint32_t rd) {
  sfor<K0, K1>([&](auto kc) {
    constexpr int k = kc.value;
    constexpr uint32_t AI = dlo(XB + k * 32, 16), BI = dlo(RB + (k * 1024 << W), 4096 << W), BH = W ? 0x40000040 : 0x80000020;
    if constexpr (k == 0 && MODE == 1) wg_ss256_t01_z<AI, BI, BH>(acc, xd, rd); else wg_ss256_t01_a<AI, BI, BH>(acc, xd, rd);
  });
}
template <int K0, int K1, bool Z>
__device__ __forceinline__ void hg64(float (&acc)[32], const uint32_t (&a)[72], uint32_t eb) {
  sfor<K0, K1>([&](auto kc) {
    constexpr int k = kc.value;
    constexpr uint32_t BI = dlo(SB + k * 2048, 8192);
    if constexpr (Z && k == K0) wg_rs64_z<BI>(acc, a[4 * k], a[4 * k + 1], a[4 * k + 2], a[4 * k + 3], eb);
    else wg_rs64_a<BI>(acc, a[4 * k], a[4 * k + 1], a[4 * k + 2], a[4 * k + 3], eb);
  });
}
__device__ __forceinline__ void out_tile(float (&c)[32], uint32_t stg, const CUtensorMap* tm, int col, int row, int lane) {
  pin(c);
  uint32_t p[16];
#pragma unroll
  for (int q = 0; q < 16; q++) p[q] = pk(c[2 * q], c[2 * q + 1]);
  if (lane == 0) asm volatile("cp.async.bulk.wait_group.read 1;" ::: "memory");
  __syncwarp();
  const int t = lane >> 3, r = lane & 7;
  const uint32_t rowa = stg + ((t & 1) * 8 + r) * 128;
#pragma unroll
  for (int q = 0; q < 4; q++) stsm4(rowa + (((2 * q + (t >> 1)) ^ r) << 4), p[4 * q], p[4 * q + 1], p[4 * q + 2], p[4 * q + 3]);
  asm volatile("fence.proxy.async.shared::cta;" ::: "memory");
  __syncwarp();
  if (lane == 0) {
    asm volatile("cp.reduce.async.bulk.tensor.2d.global.shared::cta.add.tile.bulk_group [%0, {%2,%3}], [%1];" ::"l"(tm), "r"(stg), "r"(col), "r"(row) : "memory");
    asm volatile("cp.async.bulk.commit_group;" ::: "memory");
  }
}

#define NEXT() do { sb += 8; rd = rd == 4096 ? 0 : rd + 2048; } while (0)
#define SPLIT() mbar_wait(B_XF)
#define HEAD(...) do { mbar_wait(B_F + sb); WG_FENCE(); __VA_ARGS__; WG_COMMIT(); WG_WAIT(1); REL(B_E - 8 + sb); TS(wg, 2 + (sb >> 3)); } while (0)
#define STAGE256(W) do { NEXT(); xd += 1024; HEAD((hg256<W, 0, 1>(acc, xd, rd))); hg256<W, 1, 4>(acc, xd, rd); WG_COMMIT(); } while (0)
#define P2STEP(CUR, PREV, ST) do { sb += 8; mbar_wait(B_F + sb); WG_FENCE(); \
    hg64<0, 18, true>(CUR, a, ((ETBL >> (sb & 24)) & 255) * 256); WG_COMMIT(); WG_WAIT(1); REL(B_E - 8 + sb); TS(wg, 2 + (sb >> 3)); \
    out_tile(PREV, ST, &P.t[M_OUT], col, row0, lane); col = (col + 64) & 511; } while (0)

__global__ void __launch_bounds__(NTHREADS, 1)
fused_kernel(const __grid_constant__ Params P, const __nv_bfloat16* __restrict__ gate_w, __nv_bfloat16* out) {
  extern __shared__ __align__(1024) char smem_raw[];
  const int warp = __shfl_sync(0xffffffffu, threadIdx.x >> 5, 0), lane = threadIdx.x & 31;
  const int m = blockIdx.x & 15, j = blockIdx.x >> 4;
  if ((uint32_t)__cvta_generic_to_shared(smem_raw) != SB) return;
  TS(warp >> 2, 0);
  const int rot = (j & 6) * 64;
  if (lane == 0) {
    const int grp = warp >= 8 ? warp - 8 : warp + 4;
    if (grp < 9) {
#pragma unroll
      for (int i = 0; i < 8; i++) mbar_init(BAR + grp * 64 + 8 * i, grp < 5 ? 1 : 8);
    }
    if (grp == 0) {
      asm volatile("fence.proxy.async.shared::cta;" ::: "memory");
      mbar_expect(B_XF, 32768);
      tma2(XB, &P.t[M_X], B_XF, rot, m * 128);
      tma3(RB + 65536, &P.t[M_KV], B_XF, j * 64, rot, 1);
    }
  }
  __syncthreads();
  if (warp >= 8) {
    asm volatile("setmaxnreg.dec.sync.aligned.u32 24;");
    if (warp == 8) {
      if (lane == 0) {
        asm volatile("fence.proxy.async.shared::cta;" ::: "memory");
        uint32_t dst = RB + 65536 + 16384;
#pragma unroll 1
        for (int s = 1; s < 8; s++) {
          const int k0 = (rot + s * 64) & 511;
          mbar_expect(B_XF + 8 * s, s == 7 ? 34816 : 32768);
          if (s == 7) tma2(WP, &P.t[M_WP], B_XF + 56, 0, j * 64);
          tma2(XB + s * 16384, &P.t[M_X], B_XF + 8 * s, k0, m * 128);
          if (s == 6) mbar_wait(B_E);
          tma3(dst, &P.t[M_KV], B_XF + 8 * s, j * 64, k0, 1);
          dst = dst == RB + 81920 ? RB : dst + 16384;
        }
#pragma unroll 1
        for (int s = 4; s < 20; s++) {
          mbar_wait(B_E + 8 * (s - 3));
          const uint32_t bar = B_F + 8 * s;
          mbar_expect(bar, s < 16 ? 32768 : 49152);
          const int k0 = (rot + (s < 12 ? s - 4 : s) * 64) & 511;
          if (s < 12) {
            tma4(dst + 8192, &P.t[M_GU1], bar, j * 224, k0);
            tma3(dst, &P.t[M_Q], bar, 0, k0, j * 2);
          } else {
            tma4(dst, &P.t[M_GU2], bar, j * 224 + 96, k0);
            if (s >= 16) tma2(XB + (s - 16) * 16384, &P.t[M_X], bar, k0, m * 128);
          }
          dst = dst == RB + 65536 ? RB : dst + 32768;
          if (s == m + 4) {
            if (s < 10) pf3(&P.t[M_Q], 0, (k0 + 128) & 511, j * 2);
            if (s < 18) pf4(&P.t[s < 10 ? M_GU1 : M_GU2], j * 224 + (s < 10 ? 0 : 96), (rot + (s < 10 ? s - 2 : s + 2) * 64) & 511);
          }
          if (s == (m & 7) + 8) { pf_lin(P.pf[0] + blockIdx.x * 14336, 14336); pf_lin(P.pf[1] + blockIdx.x * 4096, 4096); }
        }
#pragma unroll 1
        for (int i = 0; i < 8; i++) {
          mbar_wait(B_E + 8 * (i == 1 ? 18 : 16 + i));
          const uint32_t d = SB + ((ETBL >> (8 * (i & 3))) & 255) * 4096, bar = B_F + 8 * (20 + i);
          mbar_expect(bar, 36864);
          tma2(d + 8192, &P.t[M_WD], bar, ((j + i) & 7) * 64, j * 224);
          tma2(d, &P.t[M_WO], bar, ((j + i) & 7) * 64, j * 64);
        }
      }
    } else if (warp == 9) {
      unsigned ep;
      asm volatile("ld.relaxed.gpu.global.u32 %0, [%1];" : "=r"(ep) : "l"(&g_zcnt[m * 32]) : "memory");
      if (lane < M_N) prefetch_tm(&P.t[lane]);
      uint4* o = reinterpret_cast<uint4*>(out + (m * 128 + j * 16) * 512) + lane;
#pragma unroll 4
      for (int i = 0; i < 32; i++) o[i * 32] = make_uint4(0, 0, 0, 0);
      ep >>= 3;
      if (lane == 0) { sts32(EPS, ep); mbar_arrive(B_EP); }
      uint4* z = reinterpret_cast<uint4*>(g_kv[(ep + 1) & 1][j]) + m * 34;
      z[lane] = make_uint4(0, 0, 0, 0);
      if (lane < 2) z[32 + lane] = make_uint4(0, 0, 0, 0);
      TS2(2);
      asm volatile("fence.proxy.async.global;" ::: "memory");
      __syncwarp();
      if (lane == 0) {
        asm volatile("red.release.gpu.global.add.u32 [%0], 1;" ::"l"(&g_zcnt[m * 32]) : "memory");
        TS2(3);
        flag_wait(&g_zcnt[m * 32], (ep + 1) * 8);
        asm volatile("fence.proxy.async.global;" ::: "memory");
        mbar_arrive(B_ZK);
        TS2(4);
        mbar_wait(B_KD);
        TS2(5);
        asm volatile("red.release.gpu.global.add.u32 [%0], 1;" ::"l"(&g_kvcnt[j * 32]) : "memory");
        TS2(6);
        flag_wait(&g_kvcnt[j * 32], (ep + 1) * 16);
        TS2(7);
        mbar_arrive(B_KV);
      }
      __syncwarp();
      const float4 v = ldg_l2(g_kv[ep & 1][j] + 2048 + lane * 4);
      mbar_wait(B_E + 96);
      const uint32_t d = KI + (lane >> 2) * 768 + 512 + (lane & 3) * 64;
      sts128(d, pk(v.x, 1.f)); sts128(d + 16, pk(v.y, 1.f)); sts128(d + 32, pk(v.z, 1.f)); sts128(d + 48, pk(v.w, 1.f));
    } else {
      sts32(GW + (warp & 1) * 128 + lane * 4, __ldg(reinterpret_cast<const uint32_t*>(gate_w) + j * 32 + lane));
      __syncwarp();
      const int row = (warp & 1) * 64 + lane;
      const uint32_t xa = XB + (j & 1) * 16384 + row * 128 + ((lane & 7) << 4);
      float g[4] = {0.f, 0.f, 0.f, 0.f};
      mbar_wait(B_XF + 8 * (j & 1));
      TS2(10);
#pragma unroll 1
      for (int c = 0; c < 8; c++) {
        const uint4 w = lds128(GW + (warp & 1) * 128 + c * 16);
        g[0] = dot8(lds128(xa ^ (c << 4)), w, g[0]);
        g[1] = dot8(lds128((xa ^ (c << 4)) + 4096), w, g[1]);
      }
      g_gate[m][j][row] = g[0]; g_gate[m][j][row + 32] = g[1];
      __syncwarp();
      if (lane < 4) mbar_arrive(B_GX);
      TS2(11);
      if (lane == 0) {
        unsigned ep;
        asm volatile("atom.release.gpu.global.add.u32 %0, [%1], 1;" : "=r"(ep) : "l"(&g_zcnt[m * 32 + 8]) : "memory");
        TS2(12);
        if (warp == 10) flag_wait(&g_zcnt[m * 32 + 8], (ep & ~15u) + 16);
      }
      if (warp == 10) {
        __syncwarp();
        TS2(13);
        g[0] = 0.f; g[1] = 0.f;
#pragma unroll 2
        for (int i = 0; i < 8; i++) {
          const float4 v = ldg_l2(&g_gate[m][i][lane * 4]);
          g[0] += v.x; g[1] += v.y; g[2] += v.z; g[3] += v.w;
        }
#pragma unroll
        for (int q = 0; q < 2; q++) sts32(GV + lane * 8 + q * 4, pk(rcp(1.f + ex2(-LOG2E * g[2 * q])), rcp(1.f + ex2(-LOG2E * g[2 * q + 1]))));
        __syncwarp();
        REL(B_G);
        TS2(15);
      }
      mbar_wait(B_E + 96);
      mbar_wait(B_KV);
      const float* kp = g_kv[lds32(EPS) & 1][j] + (warp & 1) * 1024 + lane * 4;
#pragma unroll 1
      for (int h = 0; h < 2; h++) {
        float4 v[4];
#pragma unroll
        for (int i = 0; i < 4; i++) v[i] = ldg_l2(kp + h * 512 + i * 128);
        const uint32_t d = KI + (warp & 1) * 3072 + h * 1536 + lane * 4;
#pragma unroll
        for (int i = 0; i < 4; i++) { sts32(d + (i >> 1) * 768 + (i & 1) * 256, pk(v[i].x, v[i].y)); sts32(d + (i >> 1) * 768 + (i & 1) * 256 + 128, pk(v[i].z, v[i].w)); }
      }
    }
    if (warp != 8) {
      asm volatile("fence.proxy.async.shared::cta;" ::: "memory");
      __syncwarp();
      if (lane < (warp == 9 ? 2 : 3)) mbar_arrive(B_KI);
      TS2(8);
    }
  } else {
    asm volatile("setmaxnreg.inc.sync.aligned.u32 240;");
    const int wg = warp >> 2;
    const uint32_t xa = wg * 512;
    TS(wg, 1);
    uint32_t sb = 0, rd = 4096, xd = xa;
    uint32_t a[72];
    float acc[128];
    uint32_t vp[16];
#define PHI_MMA() sfor<0, 4>([&](auto tc) { constexpr int t = tc.value; wg_rs16_z<dlo(WP + t * 512, 256)>(c[t], a[4 * t], a[4 * t + 1], a[4 * t + 2], a[4 * t + 3], 0); })
#define PHI_WAIT() do { WG_WAIT(1); SPLIT(); _Pragma("unroll") for (int t = 0; t < 4; t++) pin(c[t]); } while (0)
#define BF(t, i) __float_as_uint(c[t][i])
#define BAR_WG() asm volatile("bar.sync %0, 128;" ::"r"(1 + wg) : "memory")
#define BAR_ALL() asm volatile("bar.sync 7, 256;" ::: "memory")
    {
      float ak[64];
#pragma unroll 1
      for (int s = 0; s < 8; s++) {
        mbar_wait(B_XF + sb); WG_FENCE();
        wg_ss128_t01_p<dlo(XB, 16), dlo(RB, 8192)>(ak, xd, rd, sb);
        WG_COMMIT(); WG_WAIT(1);
        if (lane == 0 && !(s & 1)) mbar_arrive(B_E - 8 + (sb >> 1));
        TS(wg, 2 + (s >> 1));
        sfor<1, 4>([&](auto kc) {
          constexpr int k = kc.value;
          wg_ss128_t01_a<dlo(XB + k * 32, 16), dlo(RB + k * 2048, 8192)>(ak, xd, rd);
        });
        WG_COMMIT();
        sb += 8; rd = rd == 5120 ? 0 : rd + 1024; xd += 1024;
      }
      sb = 32; rd = 0; xd = xa;
      HEAD((hg256<0, 0, 1, 1>(acc, xd, rd)));
      hg256<0, 1, 4>(acc, xd, rd); WG_COMMIT();
      mbar_wait(B_GX);
      pin(ak);
#pragma unroll
      for (int i = 0; i < 16; i++) { a[i] = pk(ak[2 * i], ak[2 * i + 1]); vp[i] = pk(ak[32 + 2 * i], ak[33 + 2 * i]); }
    }
    float c[4][8], mx[4][4];
    {
      const uint32_t xr = XB + (warp * 16 + (lane & 15)) * 128 + (((lane >> 4) ^ (lane & 7)) << 4);
#define PUT_V(h) do { BAR_WG(); stsm4(xr + h * 16384, vp[8 * h], vp[8 * h + 1], vp[8 * h + 2], vp[8 * h + 3]); \
      stsm4((xr ^ 32) + h * 16384, vp[8 * h + 4], vp[8 * h + 5], vp[8 * h + 6], vp[8 * h + 7]); \
      stsm4((xr ^ 64) + h * 16384, 0x3f803f80u, 0x3f803f80u, 0x3f803f80u, 0x3f803f80u); } while (0)
#define PUT_PHI(t) do { stsm4((xr ^ ((t & 1) * 64)) + (2 + (t >> 1)) * 16384, BF(t, 0), BF(t, 1), BF(t, 2), BF(t, 3)); \
      stsm4((xr ^ ((t & 1) * 64 + 32)) + (2 + (t >> 1)) * 16384, BF(t, 4), BF(t, 5), BF(t, 6), BF(t, 7)); } while (0)
      NEXT(); xd += 1024;
      HEAD({ PHI_MMA(); hg256<0, 0, 1>(acc, xd, rd); });
      hg256<0, 1, 4>(acc, xd, rd); WG_COMMIT();
      PUT_V(0);
      PHI_WAIT();
      row_max<0, 3>(c, mx);
#pragma unroll
      for (int t = 0; t < 4; t++) {
        float e[16], s[4];
        STAGE256(0); SPLIT();
        if (t == 0) { PUT_V(1); row_max<3, 4>(c, mx); }
        if (t == 1) { BAR_WG(); PUT_PHI(0); }
        if (t == 2) BAR_WG();
        row_exp(c[t], mx[t], e);
#pragma unroll
        for (int q = 0; q < 4; q++) {
          const int b = (q >> 1) * 8 + (q & 1) * 2;
          s[q] = (e[b] + e[b + 1]) + (e[b + 4] + e[b + 5]);
          s[q] += __shfl_xor_sync(0xffffffffu, s[q], 1);
        }
#pragma unroll
        for (int q = 0; q < 4; q++) s[q] = rcp(s[q] + __shfl_xor_sync(0xffffffffu, s[q], 2));
#pragma unroll
        for (int i = 0; i < 8; i++) {
          const float sc = s[(i >> 2) * 2 + (i & 1)];
          c[t][i] = __uint_as_float(pk(e[2 * i] * sc, e[2 * i + 1] * sc));
        }
        if (t) PUT_PHI(t);
      }
      asm volatile("fence.proxy.async.shared::cta;" ::: "memory");
      float kv[20];
      NEXT(); xd += 1024;
      HEAD((hg256<0, 0, 2>(acc, xd, rd)));
      BAR_ALL();
      WG_FENCE();
      sfor<0, 8>([&](auto kc) {
        constexpr int k = kc.value;
        if constexpr (k == 0) wg_ss40_t11_z<dlo(XB + 32768, 16), dlo(XB, 16)>(kv, 2 * xa, 2 * xa);
        else wg_ss40_t11_a<dlo(XB + 32768 + k * 2048, 16), dlo(XB + k * 2048, 16)>(kv, 2 * xa, 2 * xa);
      });
      WG_COMMIT();
      hg256<0, 2, 4>(acc, xd, rd); WG_COMMIT();
      WG_WAIT(1);
      mbar_wait(B_EP);
      pin(kv);
      float* dst = g_kv[lds32(EPS) & 1][j];
      const bool up = warp & 2;
#pragma unroll
      for (int i = 0; i < 2; i++)
        asm volatile("red.global.add.v4.f32 [%0], {%1,%2,%3,%4};" ::"l"(dst + warp * 256 + i * 128 + lane * 4),
                     "f"(up ? kv[8 + 4 * i] : kv[4 * i]), "f"(up ? kv[9 + 4 * i] : kv[4 * i + 1]), "f"(up ? kv[10 + 4 * i] : kv[4 * i + 2]), "f"(up ? kv[11 + 4 * i] : kv[4 * i + 3]) : "memory");
      if (!(lane & 2)) asm volatile("red.global.add.f32 [%0], %1;" ::"l"(dst + 2048 + warp * 16 + (lane & 1) * 8 + (lane >> 2)), "f"((lane & 1) ? kv[18] : kv[16]) : "memory");
      __syncwarp();
      REL(B_KD);
    }
    STAGE256(0);
    WG_WAIT(0);
    REL(B_E + sb);
    pin(acc);
#pragma unroll
    for (int i = 0; i < 16; i++) a[i] = pk(acc[2 * i], acc[2 * i + 1]);
    uint32_t h0[24];
#pragma unroll
    for (int i = 0; i < 24; i++) h0[i] = pk(acc[32 + 2 * i] * acc[80 + 2 * i], acc[33 + 2 * i] * acc[81 + 2 * i]);
    pin(h0);
    NEXT(); xd = xa + 4096;
    mbar_wait(B_F + sb); WG_FENCE();
    PHI_MMA(); WG_COMMIT();
    TS(wg, 14);
    hg256<1, 0, 4, 1>(acc, xd, rd); WG_COMMIT();
    PHI_WAIT();
    row_max<0, 2>(c, mx);
#pragma unroll
    for (int t = 0; t < 4; t++) {
      float e[16];
      if (t == 3) xd -= 8192;
      STAGE256(1); SPLIT();
      if (t == 0) row_max<2, 4>(c, mx);
      row_exp(c[t], mx[t], e);
#pragma unroll
      for (int i = 0; i < 8; i++) c[t][i] = __uint_as_float(pk(e[2 * i], e[2 * i + 1]));
      pin(c[t]);
    }
    STAGE256(1);
    mbar_wait(B_G);
    const float ga = lds_bf(GV + warp * 32 + (lane >> 2) * 2), gb = lds_bf(GV + warp * 32 + 16 + (lane >> 2) * 2);
    mbar_wait(B_KI);
    TS(wg, 34);
    sfor<0, 4>([&](auto tc) {
      constexpr int t = tc.value;
      float p[12], q[12];
#define O_MMA() do { wg_rs24_z<dlo(KI + t * 1536, 128)>(p, BF(t, 0), BF(t, 1), BF(t, 2), BF(t, 3), 0); \
                     wg_rs24_z<dlo(KI + t * 1536 + 768, 128)>(q, BF(t, 4), BF(t, 5), BF(t, 6), BF(t, 7), 0); } while (0)
      if constexpr (t & 1) {
        WG_FENCE(); O_MMA(); WG_COMMIT();
        hg256<1, 2, 4>(acc, xd, rd);
      } else {
        NEXT(); xd += 1024;
        HEAD({ O_MMA(); hg256<1, 0, 1>(acc, xd, rd); });
        hg256<1, 1, 2>(acc, xd, rd);
      }
      WG_COMMIT(); WG_WAIT(1); SPLIT();
      pin(p); pin(q);
      const float ra = ga * rcp(fmaf(fmaf(1e-6f, p[9], p[8]), q[9], q[8] * p[9]));
      const float rb = gb * rcp(fmaf(fmaf(1e-6f, p[11], p[10]), q[11], q[10] * p[11]));
      const float pa_ = ra * q[9], na_ = ra * p[9], pb_ = rb * q[11], nb_ = rb * p[11];
#pragma unroll
      for (int i = 0; i < 4; i++) {
        const float sp = (i & 1) ? pb_ : pa_, sn = (i & 1) ? nb_ : na_;
        a[4 * t + i] = pk(fmaf(p[2 * i], sp, q[2 * i] * sn), fmaf(p[2 * i + 1], sp, q[2 * i + 1] * sn));
      }
    });
    pin(h0);
#pragma unroll
    for (int i = 0; i < 24; i++) a[16 + i] = hmul2(h0[i], (i & 1) ? pk(1.f - gb, 1.f - gb) : pk(1.f - ga, 1.f - ga));
    float pa[32], pb[32];
    sb += 8;
    HEAD((hg64<0, 4, true>(pa, a, (ETBL & 255) * 256)));
    hg64<4, 10, false>(pa, a, (ETBL & 255) * 256);
    SPLIT();
    pin(acc);
    gu_pack<0, 64, 40, 16>(acc, a, 1.f - ga, 1.f - gb);
    WG_FENCE();
    hg64<10, 14, false>(pa, a, (ETBL & 255) * 256);
    SPLIT();
    gu_pack<32, 96, 56, 16>(acc, a, 1.f - ga, 1.f - gb);
    WG_FENCE();
    hg64<14, 18, false>(pa, a, (ETBL & 255) * 256);
    WG_COMMIT();
    const uint32_t stg = STG + warp * 2048;
    const int row0 = m * 128 + warp * 16;
    int col = j * 64;
    mbar_wait(B_ZK);
    mbar_wait(B_E + 8 * 19);
#pragma unroll 1
    for (int it = 0; it < 3; it++) {
      P2STEP(pb, pa, stg);
      P2STEP(pa, pb, stg + 16384);
    }
    P2STEP(pb, pa, stg);
    WG_WAIT(0);
    TS(wg, 30);
    out_tile(pb, stg + 16384, &P.t[M_OUT], col, row0, lane);
    if (lane == 0) asm volatile("cp.async.bulk.wait_group.read 0;" ::: "memory");
    TS(wg, 31);
  }
}

typedef CUresult (*EncFn)(CUtensorMap*, CUtensorMapDataType, cuuint32_t, void*, const cuuint64_t*, const cuuint64_t*, const cuuint32_t*, const cuuint32_t*,
                          CUtensorMapInterleave, CUtensorMapSwizzle, CUtensorMapL2promotion, CUtensorMapFloatOOBfill);

void enc(EncFn fn, CUtensorMap* t, const void* p, int rank, cuuint64_t d0, cuuint64_t d1, cuuint64_t d2, cuuint64_t s1, cuuint64_t s2, cuuint32_t b0, cuuint32_t b1, cuuint32_t b2, cuuint64_t s3 = 0) {
  const cuuint64_t gd[4] = {d0, d1, d2, 2}, gs[3] = {s1, s2, s3};
  const cuuint32_t bd[4] = {b0, b1, b2, 2}, es[4] = {1, 1, 1, 1};
  fn(t, CU_TENSOR_MAP_DATA_TYPE_BFLOAT16, rank, const_cast<void*>(p), gd, gs, bd, es, CU_TENSOR_MAP_INTERLEAVE_NONE, b0 == 16 ? CU_TENSOR_MAP_SWIZZLE_32B : b0 == 32 ? CU_TENSOR_MAP_SWIZZLE_64B : CU_TENSOR_MAP_SWIZZLE_128B,
     CU_TENSOR_MAP_L2_PROMOTION_L2_256B, CU_TENSOR_MAP_FLOAT_OOB_FILL_NONE);
}

}

extern "C" void kernel_launch(void* const* d_in, const int* in_sizes, int n_in, void* d_out, int out_size) {
  void* fp = nullptr;
  cudaDriverEntryPointQueryResult qr;
  cudaGetDriverEntryPoint("cuTensorMapEncodeTiled", &fp, cudaEnableDefault, &qr);
  EncFn fn = (EncFn)fp;
  Params P;
  enc(fn, &P.t[M_X], d_in[0], 2, 512, 2048, 1, 1024, 0, 64, 128, 1);
  enc(fn, &P.t[M_KV], d_in[1], 3, 512, 512, 3, 3072, 1024, 64, 64, 2);
  enc(fn, &P.t[M_Q], d_in[1], 3, 32, 512, 16, 3072, 64, 32, 64, 2);
  const char *pg = (const char*)d_in[5], *pu = (const char*)d_in[6];
  const char* lo = pg < pu ? pg : pu;
  const cuuint64_t dist = pg < pu ? pu - pg : pg - pu;
  enc(fn, &P.t[M_GU1], lo, 4, 1792 - 64, 512, 3, 3584, 64, 32, 64, 3, dist);
  enc(fn, &P.t[M_GU2], lo, 4, 1792 - 64, 512, 2, 3584, 128, 64, 64, 2, dist);
  enc(fn, &P.t[M_WO], d_in[3], 2, 512, 512, 1, 1024, 0, 64, 64, 1);
  enc(fn, &P.t[M_WD], d_in[7], 2, 512, 1792, 1, 1024, 0, 64, 224, 1);
  enc(fn, &P.t[M_OUT], d_out, 2, 512, 2048, 1, 1024, 0, 64, 16, 1);
  enc(fn, &P.t[M_WP], d_in[2], 2, 16, 512, 1, 32, 0, 16, 64, 1);
  P.pf[0] = (const char*)d_in[7]; P.pf[1] = (const char*)d_in[3];
  cudaFuncSetAttribute(fused_kernel, cudaFuncAttributeMaxDynamicSharedMemorySize, SMEM_BYTES);
  fused_kernel<<<128, NTHREADS, SMEM_BYTES>>>(P, (const __nv_bfloat16*)d_in[8], (__nv_bfloat16*)d_out);
}
```

```cpp
#include <cuda_runtime.h>
#include <cuda.h>
#include <cuda_bf16.h>
#include <stdint.h>
#include <type_traits>

template <uint32_t AI, uint32_t BI, uint32_t BH = 0x40000040> __device__ __forceinline__ void wg_ss256_t01_z(float (&d)[128], uint32_t ab, uint32_t bb) {
  asm volatile("{\n.reg .pred p;\n.reg .b32 t, u;\n.reg .b64 da, db;\nsetp.ne.b32 p, 0, 0;\nadd.u32 t, %128, %130;\nadd.u32 u, %129, %131;\n"
    "mov.b64 da, {t, 0x40000040};\nmov.b64 db, {u, %132};\n"
    "wgmma.mma_async.sync.aligned.m64n256k16.f32.bf16.bf16 "
    "{%0, %1, %2, %3, %4, %5, %6, %7, %8, %9, %10, %11, %12, %13, %14, %15, %16, %17, %18, %19, %20, %21, %22, %23, %24, %25, %26, %27, %28, %29, %30, %31, %32, %33, %34, %35, %36, %37, %38, %39, %40, %41, %42, %43, %44, %45, %46, %47, %48, %49, %50, %51, %52, %53, %54, %55, %56, %57, %58, %59, %60, %61, %62, %63, %64, %65, %66, %67, %68, %69, %70, %71, %72, %73, %74, %75, %76, %77, %78, %79, %80, %81, %82, %83, %84, %85, %86, %87, %88, %89, %90, %91, %92, %93, %94, %95, %96, %97, %98, %99, %100, %101, %102, %103, %104, %105, %106, %107, %108, %109, %110, %111, %112, %113, %114, %115, %116, %117, %118, %119, %120, %121, %122, %123, %124, %125, %126, %127}, da, db, p, 1, 1, 0, 1;\n}\n"
    : "=f"(d[0]), "=f"(d[1]), "=f"(d[2]), "=f"(d[3]), "=f"(d[4]), "=f"(d[5]), "=f"(d[6]), "=f"(d[7]), "=f"(d[8]), "=f"(d[9]), "=f"(d[10]), "=f"(d[11]), "=f"(d[12]), "=f"(d[13]), "=f"(d[14]), "=f"(d[15]), "=f"(d[16]), "=f"(d[17]), "=f"(d[18]), "=f"(d[19]), "=f"(d[20]), "=f"(d[21]), "=f"(d[22]), "=f"(d[23]), "=f"(d[24]), "=f"(d[25]), "=f"(d[26]), "=f"(d[27]), "=f"(d[28]), "=f"(d[29]), "=f"(d[30]), "=f"(d[31]), "=f"(d[32]), "=f"(d[33]), "=f"(d[34]), "=f"(d[35]), "=f"(d[36]), "=f"(d[37]), "=f"(d[38]), "=f"(d[39]), "=f"(d[40]), "=f"(d[41]), "=f"(d[42]), "=f"(d[43]), "=f"(d[44]), "=f"(d[45]), "=f"(d[46]), "=f"(d[47]), "=f"(d[48]), "=f"(d[49]), "=f"(d[50]), "=f"(d[51]), "=f"(d[52]), "=f"(d[53]), "=f"(d[54]), "=f"(d[55]), "=f"(d[56]), "=f"(d[57]), "=f"(d[58]), "=f"(d[59]), "=f"(d[60]), "=f"(d[61]), "=f"(d[62]), "=f"(d[63]), "=f"(d[64]), "=f"(d[65]), "=f"(d[66]), "=f"(d[67]), "=f"(d[68]), "=f"(d[69]), "=f"(d[70]), "=f"(d[71]), "=f"(d[72]), "=f"(d[73]), "=f"(d[74]), "=f"(d[75]), "=f"(d[76]), "=f"(d[77]), "=f"(d[78]), "=f"(d[79]), "=f"(d[80]), "=f"(d[81]), "=f"(d[82]), "=f"(d[83]), "=f"(d[84]), "=f"(d[85]), "=f"(d[86]), "=f"(d[87]), "=f"(d[88]), "=f"(d[89]), "=f"(d[90]), "=f"(d[91]), "=f"(d[92]), "=f"(d[93]), "=f"(d[94]), "=f"(d[95]), "=f"(d[96]), "=f"(d[97]), "=f"(d[98]), "=f"(d[99]), "=f"(d[100]), "=f"(d[101]), "=f"(d[102]), "=f"(d[103]), "=f"(d[104]), "=f"(d[105]), "=f"(d[106]), "=f"(d[107]), "=f"(d[108]), "=f"(d[109]), "=f"(d[110]), "=f"(d[111]), "=f"(d[112]), "=f"(d[113]), "=f"(d[114]), "=f"(d[115]), "=f"(d[116]), "=f"(d[117]), "=f"(d[118]), "=f"(d[119]), "=f"(d[120]), "=f"(d[121]), "=f"(d[122]), "=f"(d[123]), "=f"(d[124]), "=f"(d[125]), "=f"(d[126]), "=f"(d[127])
    : "r"(ab), "r"(bb), "n"(AI), "n"(BI), "n"(BH));
}
template <uint32_t AI, uint32_t BI, uint32_t BH = 0x40000040> __device__ __forceinline__ void wg_ss256_t01_a(float (&d)[128], uint32_t ab, uint32_t bb) {
  asm volatile("{\n.reg .pred p;\n.reg .b32 t, u;\n.reg .b64 da, db;\nsetp.ne.b32 p, 1, 0;\nadd.u32 t, %128, %130;\nadd.u32 u, %129, %131;\n"
    "mov.b64 da, {t, 0x40000040};\nmov.b64 db, {u, %132};\n"
    "wgmma.mma_async.sync.aligned.m64n256k16.f32.bf16.bf16 "
    "{%0, %1, %2, %3, %4, %5, %6, %7, %8, %9, %10, %11, %12, %13, %14, %15, %16, %17, %18, %19, %20, %21, %22, %23, %24, %25, %26, %27, %28, %29, %30, %31, %32, %33, %34, %35, %36, %37, %38, %39, %40, %41, %42, %43, %44, %45, %46, %47, %48, %49, %50, %51, %52, %53, %54, %55, %56, %57, %58, %59, %60, %61, %62, %63, %64, %65, %66, %67, %68, %69, %70, %71, %72, %73, %74, %75, %76, %77, %78, %79, %80, %81, %82, %83, %84, %85, %86, %87, %88, %89, %90, %91, %92, %93, %94, %95, %96, %97, %98, %99, %100, %101, %102, %103, %104, %105, %106, %107, %108, %109, %110, %111, %112, %113, %114, %115, %116, %117, %118, %119, %120, %121, %122, %123, %124, %125, %126, %127}, da, db, p, 1, 1, 0, 1;\n}\n"
    : "+f"(d[0]), "+f"(d[1]), "+f"(d[2]), "+f"(d[3]), "+f"(d[4]), "+f"(d[5]), "+f"(d[6]), "+f"(d[7]), "+f"(d[8]), "+f"(d[9]), "+f"(d[10]), "+f"(d[11]), "+f"(d[12]), "+f"(d[13]), "+f"(d[14]), "+f"(d[15]), "+f"(d[16]), "+f"(d[17]), "+f"(d[18]), "+f"(d[19]), "+f"(d[20]), "+f"(d[21]), "+f"(d[22]), "+f"(d[23]), "+f"(d[24]), "+f"(d[25]), "+f"(d[26]), "+f"(d[27]), "+f"(d[28]), "+f"(d[29]), "+f"(d[30]), "+f"(d[31]), "+f"(d[32]), "+f"(d[33]), "+f"(d[34]), "+f"(d[35]), "+f"(d[36]), "+f"(d[37]), "+f"(d[38]), "+f"(d[39]), "+f"(d[40]), "+f"(d[41]), "+f"(d[42]), "+f"(d[43]), "+f"(d[44]), "+f"(d[45]), "+f"(d[46]), "+f"(d[47]), "+f"(d[48]), "+f"(d[49]), "+f"(d[50]), "+f"(d[51]), "+f"(d[52]), "+f"(d[53]), "+f"(d[54]), "+f"(d[55]), "+f"(d[56]), "+f"(d[57]), "+f"(d[58]), "+f"(d[59]), "+f"(d[60]), "+f"(d[61]), "+f"(d[62]), "+f"(d[63]), "+f"(d[64]), "+f"(d[65]), "+f"(d[66]), "+f"(d[67]), "+f"(d[68]), "+f"(d[69]), "+f"(d[70]), "+f"(d[71]), "+f"(d[72]), "+f"(d[73]), "+f"(d[74]), "+f"(d[75]), "+f"(d[76]), "+f"(d[77]), "+f"(d[78]), "+f"(d[79]), "+f"(d[80]), "+f"(d[81]), "+f"(d[82]), "+f"(d[83]), "+f"(d[84]), "+f"(d[85]), "+f"(d[86]), "+f"(d[87]), "+f"(d[88]), "+f"(d[89]), "+f"(d[90]), "+f"(d[91]), "+f"(d[92]), "+f"(d[93]), "+f"(d[94]), "+f"(d[95]), "+f"(d[96]), "+f"(d[97]), "+f"(d[98]), "+f"(d[99]), "+f"(d[100]), "+f"(d[101]), "+f"(d[102]), "+f"(d[103]), "+f"(d[104]), "+f"(d[105]), "+f"(d[106]), "+f"(d[107]), "+f"(d[108]), "+f"(d[109]), "+f"(d[110]), "+f"(d[111]), "+f"(d[112]), "+f"(d[113]), "+f"(d[114]), "+f"(d[115]), "+f"(d[116]), "+f"(d[117]), "+f"(d[118]), "+f"(d[119]), "+f"(d[120]), "+f"(d[121]), "+f"(d[122]), "+f"(d[123]), "+f"(d[124]), "+f"(d[125]), "+f"(d[126]), "+f"(d[127])
    : "r"(ab), "r"(bb), "n"(AI), "n"(BI), "n"(BH));
}
template <uint32_t AI, uint32_t BI, uint32_t BH = 0x40000040> __device__ __forceinline__ void wg_ss128_t01_a(float (&d)[64], uint32_t ab, uint32_t bb) {
  asm volatile("{\n.reg .pred p;\n.reg .b32 t, u;\n.reg .b64 da, db;\nsetp.ne.b32 p, 1, 0;\nadd.u32 t, %64, %66;\nadd.u32 u, %65, %67;\n"
    "mov.b64 da, {t, 0x40000040};\nmov.b64 db, {u, %68};\n"
    "wgmma.mma_async.sync.aligned.m64n128k16.f32.bf16.bf16 "
    "{%0, %1, %2, %3, %4, %5, %6, %7, %8, %9, %10, %11, %12, %13, %14, %15, %16, %17, %18, %19, %20, %21, %22, %23, %24, %25, %26, %27, %28, %29, %30, %31, %32, %33, %34, %35, %36, %37, %38, %39, %40, %41, %42, %43, %44, %45, %46, %47, %48, %49, %50, %51, %52, %53, %54, %55, %56, %57, %58, %59, %60, %61, %62, %63}, da, db, p, 1, 1, 0, 1;\n}\n"
    : "+f"(d[0]), "+f"(d[1]), "+f"(d[2]), "+f"(d[3]), "+f"(d[4]), "+f"(d[5]), "+f"(d[6]), "+f"(d[7]), "+f"(d[8]), "+f"(d[9]), "+f"(d[10]), "+f"(d[11]), "+f"(d[12]), "+f"(d[13]), "+f"(d[14]), "+f"(d[15]), "+f"(d[16]), "+f"(d[17]), "+f"(d[18]), "+f"(d[19]), "+f"(d[20]), "+f"(d[21]), "+f"(d[22]), "+f"(d[23]), "+f"(d[24]), "+f"(d[25]), "+f"(d[26]), "+f"(d[27]), "+f"(d[28]), "+f"(d[29]), "+f"(d[30]), "+f"(d[31]), "+f"(d[32]), "+f"(d[33]), "+f"(d[34]), "+f"(d[35]), "+f"(d[36]), "+f"(d[37]), "+f"(d[38]), "+f"(d[39]), "+f"(d[40]), "+f"(d[41]), "+f"(d[42]), "+f"(d[43]), "+f"(d[44]), "+f"(d[45]), "+f"(d[46]), "+f"(d[47]), "+f"(d[48]), "+f"(d[49]), "+f"(d[50]), "+f"(d[51]), "+f"(d[52]), "+f"(d[53]), "+f"(d[54]), "+f"(d[55]), "+f"(d[56]), "+f"(d[57]), "+f"(d[58]), "+f"(d[59]), "+f"(d[60]), "+f"(d[61]), "+f"(d[62]), "+f"(d[63])
    : "r"(ab), "r"(bb), "n"(AI), "n"(BI), "n"(BH));
}
template <uint32_t AI, uint32_t BI, uint32_t BH = 0x40000040> __device__ __forceinline__ void wg_ss128_t01_p(float (&d)[64], uint32_t ab, uint32_t bb, uint32_t sd) {
  asm volatile("{\n.reg .pred p;\n.reg .b32 t, u;\n.reg .b64 da, db;\nsetp.ne.b32 p, %69, 0;\nadd.u32 t, %64, %66;\nadd.u32 u, %65, %67;\n"
    "mov.b64 da, {t, 0x40000040};\nmov.b64 db, {u, %68};\n"
    "wgmma.mma_async.sync.aligned.m64n128k16.f32.bf16.bf16 "
    "{%0, %1, %2, %3, %4, %5, %6, %7, %8, %9, %10, %11, %12, %13, %14, %15, %16, %17, %18, %19, %20, %21, %22, %23, %24, %25, %26, %27, %28, %29, %30, %31, %32, %33, %34, %35, %36, %37, %38, %39, %40, %41, %42, %43, %44, %45, %46, %47, %48, %49, %50, %51, %52, %53, %54, %55, %56, %57, %58, %59, %60, %61, %62, %63}, da, db, p, 1, 1, 0, 1;\n}\n"
    : "+f"(d[0]), "+f"(d[1]), "+f"(d[2]), "+f"(d[3]), "+f"(d[4]), "+f"(d[5]), "+f"(d[6]), "+f"(d[7]), "+f"(d[8]), "+f"(d[9]), "+f"(d[10]), "+f"(d[11]), "+f"(d[12]), "+f"(d[13]), "+f"(d[14]), "+f"(d[15]), "+f"(d[16]), "+f"(d[17]), "+f"(d[18]), "+f"(d[19]), "+f"(d[20]), "+f"(d[21]), "+f"(d[22]), "+f"(d[23]), "+f"(d[24]), "+f"(d[25]), "+f"(d[26]), "+f"(d[27]), "+f"(d[28]), "+f"(d[29]), "+f"(d[30]), "+f"(d[31]), "+f"(d[32]), "+f"(d[33]), "+f"(d[34]), "+f"(d[35]), "+f"(d[36]), "+f"(d[37]), "+f"(d[38]), "+f"(d[39]), "+f"(d[40]), "+f"(d[41]), "+f"(d[42]), "+f"(d[43]), "+f"(d[44]), "+f"(d[45]), "+f"(d[46]), "+f"(d[47]), "+f"(d[48]), "+f"(d[49]), "+f"(d[50]), "+f"(d[51]), "+f"(d[52]), "+f"(d[53]), "+f"(d[54]), "+f"(d[55]), "+f"(d[56]), "+f"(d[57]), "+f"(d[58]), "+f"(d[59]), "+f"(d[60]), "+f"(d[61]), "+f"(d[62]), "+f"(d[63])
    : "r"(ab), "r"(bb), "n"(AI), "n"(BI), "n"(BH), "r"(sd));
}
template <uint32_t BI> __device__ __forceinline__ void wg_rs16_z(float (&d)[8], uint32_t a0, uint32_t a1, uint32_t a2, uint32_t a3, uint32_t bb) {
  asm volatile("{\n.reg .pred p;\n.reg .b32 u;\n.reg .b64 db;\nsetp.ne.b32 p, 0, 0;\nadd.u32 u, %12, %13;\nmov.b64 db, {u, 0xC0000010};\n"
    "wgmma.mma_async.sync.aligned.m64n16k16.f32.bf16.bf16 "
    "{%0, %1, %2, %3, %4, %5, %6, %7}, {%8, %9, %10, %11}, db, p, 1, 1, 1;\n}\n"
    : "=f"(d[0]), "=f"(d[1]), "=f"(d[2]), "=f"(d[3]), "=f"(d[4]), "=f"(d[5]), "=f"(d[6]), "=f"(d[7])
    : "r"(a0), "r"(a1), "r"(a2), "r"(a3), "r"(bb), "n"(BI));
}
template <uint32_t BI> __device__ __forceinline__ void wg_rs24_z(float (&d)[12], uint32_t a0, uint32_t a1, uint32_t a2, uint32_t a3, uint32_t bb) {
  asm volatile("{\n.reg .pred p;\n.reg .b32 u;\n.reg .b64 db;\nsetp.ne.b32 p, 0, 0;\nadd.u32 u, %16, %17;\nmov.b64 db, {u, 0x00000010};\n"
    "wgmma.mma_async.sync.aligned.m64n24k16.f32.bf16.bf16 "
    "{%0, %1, %2, %3, %4, %5, %6, %7, %8, %9, %10, %11}, {%12, %13, %14, %15}, db, p, 1, 1, 1;\n}\n"
    : "=f"(d[0]), "=f"(d[1]), "=f"(d[2]), "=f"(d[3]), "=f"(d[4]), "=f"(d[5]), "=f"(d[6]), "=f"(d[7]), "=f"(d[8]), "=f"(d[9]), "=f"(d[10]), "=f"(d[11])
    : "r"(a0), "r"(a1), "r"(a2), "r"(a3), "r"(bb), "n"(BI));
}
template <uint32_t AI, uint32_t BI, uint32_t BH = 0x40000040> __device__ __forceinline__ void wg_ss40_t01_z(float (&d)[20], uint32_t ab, uint32_t bb) {
  asm volatile("{\n.reg .pred p;\n.reg .b32 t, u;\n.reg .b64 da, db;\nsetp.ne.b32 p, 0, 0;\nadd.u32 t, %20, %22;\nadd.u32 u, %21, %23;\n"
    "mov.b64 da, {t, 0x40000040};\nmov.b64 db, {u, %24};\n"
    "wgmma.mma_async.sync.aligned.m64n40k16.f32.bf16.bf16 "
    "{%0, %1, %2, %3, %4, %5, %6, %7, %8, %9, %10, %11, %12, %13, %14, %15, %16, %17, %18, %19}, da, db, p, 1, 1, 0, 1;\n}\n"
    : "=f"(d[0]), "=f"(d[1]), "=f"(d[2]), "=f"(d[3]), "=f"(d[4]), "=f"(d[5]), "=f"(d[6]), "=f"(d[7]), "=f"(d[8]), "=f"(d[9]), "=f"(d[10]), "=f"(d[11]), "=f"(d[12]), "=f"(d[13]), "=f"(d[14]), "=f"(d[15]), "=f"(d[16]), "=f"(d[17]), "=f"(d[18]), "=f"(d[19])
    : "r"(ab), "r"(bb), "n"(AI), "n"(BI), "n"(BH));
}
template <uint32_t AI, uint32_t BI, uint32_t BH = 0x40000040> __device__ __forceinline__ void wg_ss40_t01_a(float (&d)[20], uint32_t ab, uint32_t bb) {
  asm volatile("{\n.reg .pred p;\n.reg .b32 t, u;\n.reg .b64 da, db;\nsetp.ne.b32 p, 1, 0;\nadd.u32 t, %20, %22;\nadd.u32 u, %21, %23;\n"
    "mov.b64 da, {t, 0x40000040};\nmov.b64 db, {u, %24};\n"
    "wgmma.mma_async.sync.aligned.m64n40k16.f32.bf16.bf16 "
    "{%0, %1, %2, %3, %4, %5, %6, %7, %8, %9, %10, %11, %12, %13, %14, %15, %16, %17, %18, %19}, da, db, p, 1, 1, 0, 1;\n}\n"
    : "+f"(d[0]), "+f"(d[1]), "+f"(d[2]), "+f"(d[3]), "+f"(d[4]), "+f"(d[5]), "+f"(d[6]), "+f"(d[7]), "+f"(d[8]), "+f"(d[9]), "+f"(d[10]), "+f"(d[11]), "+f"(d[12]), "+f"(d[13]), "+f"(d[14]), "+f"(d[15]), "+f"(d[16]), "+f"(d[17]), "+f"(d[18]), "+f"(d[19])
    : "r"(ab), "r"(bb), "n"(AI), "n"(BI), "n"(BH));
}
template <uint32_t BI> __device__ __forceinline__ void wg_rs64_z(float (&d)[32], uint32_t a0, uint32_t a1, uint32_t a2, uint32_t a3, uint32_t bb) {
  asm volatile("{\n.reg .pred p;\n.reg .b32 u;\n.reg .b64 db;\nsetp.ne.b32 p, 0, 0;\nadd.u32 u, %36, %37;\nmov.b64 db, {u, 0x40000040};\n"
    "wgmma.mma_async.sync.aligned.m64n64k16.f32.bf16.bf16 "
    "{%0, %1, %2, %3, %4, %5, %6, %7, %8, %9, %10, %11, %12, %13, %14, %15, %16, %17, %18, %19, %20, %21, %22, %23, %24, %25, %26, %27, %28, %29, %30, %31}, {%32, %33, %34, %35}, db, p, 1, 1, 1;\n}\n"
    : "=f"(d[0]), "=f"(d[1]), "=f"(d[2]), "=f"(d[3]), "=f"(d[4]), "=f"(d[5]), "=f"(d[6]), "=f"(d[7]), "=f"(d[8]), "=f"(d[9]), "=f"(d[10]), "=f"(d[11]), "=f"(d[12]), "=f"(d[13]), "=f"(d[14]), "=f"(d[15]), "=f"(d[16]), "=f"(d[17]), "=f"(d[18]), "=f"(d[19]), "=f"(d[20]), "=f"(d[21]), "=f"(d[22]), "=f"(d[23]), "=f"(d[24]), "=f"(d[25]), "=f"(d[26]), "=f"(d[27]), "=f"(d[28]), "=f"(d[29]), "=f"(d[30]), "=f"(d[31])
    : "r"(a0), "r"(a1), "r"(a2), "r"(a3), "r"(bb), "n"(BI));
}
template <uint32_t BI> __device__ __forceinline__ void wg_rs64_a(float (&d)[32], uint32_t a0, uint32_t a1, uint32_t a2, uint32_t a3, uint32_t bb) {
  asm volatile("{\n.reg .pred p;\n.reg .b32 u;\n.reg .b64 db;\nsetp.ne.b32 p, 1, 0;\nadd.u32 u, %36, %37;\nmov.b64 db, {u, 0x40000040};\n"
    "wgmma.mma_async.sync.aligned.m64n64k16.f32.bf16.bf16 "
    "{%0, %1, %2, %3, %4, %5, %6, %7, %8, %9, %10, %11, %12, %13, %14, %15, %16, %17, %18, %19, %20, %21, %22, %23, %24, %25, %26, %27, %28, %29, %30, %31}, {%32, %33, %34, %35}, db, p, 1, 1, 1;\n}\n"
    : "+f"(d[0]), "+f"(d[1]), "+f"(d[2]), "+f"(d[3]), "+f"(d[4]), "+f"(d[5]), "+f"(d[6]), "+f"(d[7]), "+f"(d[8]), "+f"(d[9]), "+f"(d[10]), "+f"(d[11]), "+f"(d[12]), "+f"(d[13]), "+f"(d[14]), "+f"(d[15]), "+f"(d[16]), "+f"(d[17]), "+f"(d[18]), "+f"(d[19]), "+f"(d[20]), "+f"(d[21]), "+f"(d[22]), "+f"(d[23]), "+f"(d[24]), "+f"(d[25]), "+f"(d[26]), "+f"(d[27]), "+f"(d[28]), "+f"(d[29]), "+f"(d[30]), "+f"(d[31])
    : "r"(a0), "r"(a1), "r"(a2), "r"(a3), "r"(bb), "n"(BI));
}

#define ROTM 0
#define PFS 9
#define K1 4
#define K2 8
#define OE 1
#define PH 3
#define S1 3
#define R1 8
#define R2 11
#define R3 15
#define USECL 1
#define NF 2
#define NA 1
#define PO 0
#define PX 2
#define PA 1
#define PW 2
#define DL 9
#define ZD 0
#define ZS 8
namespace {

constexpr uint32_t SB = 1024;
constexpr uint32_t XB = SB;
constexpr uint32_t RB = SB + 131072;
constexpr uint32_t MISC = RB + 98304;
constexpr uint32_t WP = MISC;
constexpr uint32_t GV = MISC + 2048;
constexpr uint32_t GW = GV;
constexpr uint32_t BAR = MISC + 2304;
constexpr uint32_t B_XF = BAR;
constexpr uint32_t B_F = BAR + 8 * 8;
constexpr uint32_t B_KV = BAR + 36 * 8;
constexpr uint32_t B_ZK = BAR + 37 * 8;
constexpr uint32_t B_G = BAR + 38 * 8;
constexpr uint32_t B_EP = BAR + 39 * 8;
constexpr uint32_t B_E = BAR + 41 * 8;
constexpr uint32_t KI = XB + 65536;
constexpr uint32_t KF = KI + 6144;
constexpr uint32_t B_GX = BAR + 69 * 8;
constexpr uint32_t B_KD = BAR + 70 * 8;
constexpr uint32_t B_KI = BAR + 71 * 8;
constexpr uint32_t B_RX = BAR + 72 * 8;
constexpr uint32_t B_PR = BAR + 40 * 8;
constexpr uint32_t EPS = BAR + 80 * 8;
constexpr uint32_t RX = SB + 36 * 4096;
constexpr int SMEM_BYTES = 131072 + 98304 + 3072;
constexpr int NTHREADS = 384;
constexpr uint32_t ETBL = 0x1B280012u;
constexpr uint32_t STG = SB + 36864;

enum { M_X, M_KV, M_Q, M_GU1, M_GU2, M_WO, M_WD, M_OUT, M_WP, M_N };
struct Params { CUtensorMap t[M_N]; const char* pf[2]; };

__device__ float g_kv[2][8][2176];
__device__ float g_gate[16][8][128];
__device__ unsigned g_kvcnt[8 * 32];
__device__ unsigned g_zcnt[16 * 32];
#define TS(w, i) do {} while (0)
#define TS2(i) do {} while (0)

extern __shared__ __align__(1024) char smem_raw[];
__device__ __forceinline__ uint32_t own() { return (uint32_t)__cvta_generic_to_shared(smem_raw) - SB; }
__device__ __forceinline__ void mbar_init(uint32_t bar, int cnt) { asm volatile("mbarrier.init.shared::cta.b64 [%0], %1;" ::"r"(bar + own()), "r"(cnt)); }
__device__ __forceinline__ void mbar_expect(uint32_t bar, uint32_t bytes) {
  asm volatile("mbarrier.arrive.expect_tx.shared::cta.b64 _, [%0], %1;" ::"r"(bar + own()), "r"(bytes) : "memory");
}
__device__ __forceinline__ void mbar_arrive(uint32_t bar) { asm volatile("mbarrier.arrive.shared::cta.b64 _, [%0];" ::"r"(bar + own()) : "memory"); }
__device__ __forceinline__ void mbar_wait(uint32_t bar) {
  asm volatile(
      "{\n.reg .pred p;\n.reg .u32 c;\nmov.u32 c, 0;\n"
      "LW%=:\nmbarrier.try_wait.parity.shared::cta.b64 p, [%0], 0;\n@p bra LD%=;\n"
      "add.u32 c, c, 1;\nsetp.lt.u32 p, c, 2097152;\n@p bra LW%=;\ntrap;\nLD%=:\n}" ::"r"(bar + own()) : "memory");
}
__device__ __forceinline__ void flag_wait(const unsigned* p, unsigned target) {
  asm volatile(
      "{\n.reg .pred p;\n.reg .u32 c, v;\nmov.u32 c, 0;\n"
      "LW%=:\nld.acquire.gpu.global.u32 v, [%0];\nsub.u32 v, v, %1;\nsetp.ge.s32 p, v, 0;\n@p bra LD%=;\n"
      "add.u32 c, c, 1;\nsetp.lt.u32 p, c, 2097152;\n@p bra LW%=;\ntrap;\nLD%=:\n}" ::"l"(p), "r"(target) : "memory");
}
__device__ __forceinline__ void tma3(uint32_t dst, const CUtensorMap* m, uint32_t bar, int c0, int c1, int c2) {
  asm volatile("cp.async.bulk.tensor.3d.shared::cluster.global.mbarrier::complete_tx::bytes [%0], [%1, {%3,%4,%5}], [%2];" ::"r"(dst + own()), "l"(m), "r"(bar + own()), "r"(c0), "r"(c1), "r"(c2) : "memory");
}
__device__ __forceinline__ void tma4(uint32_t dst, const CUtensorMap* m, uint32_t bar, int c0, int c1) {
  asm volatile("cp.async.bulk.tensor.4d.shared::cluster.global.mbarrier::complete_tx::bytes [%0], [%1, {%3,%4,%5,%5}], [%2];" ::"r"(dst + own()), "l"(m), "r"(bar + own()), "r"(c0), "r"(c1), "r"(0) : "memory");
}
__device__ __forceinline__ void tma2(uint32_t dst, const CUtensorMap* m, uint32_t bar, int c0, int c1) {
  asm volatile("cp.async.bulk.tensor.2d.shared::cluster.global.mbarrier::complete_tx::bytes [%0], [%1, {%3,%4}], [%2];" ::"r"(dst + own()), "l"(m), "r"(bar + own()), "r"(c0), "r"(c1) : "memory");
}
__device__ __forceinline__ void pf3(const CUtensorMap* m, int c0, int c1, int c2) {
  asm volatile("cp.async.bulk.prefetch.tensor.3d.L2.global [%0, {%1,%2,%3}];" ::"l"(m), "r"(c0), "r"(c1), "r"(c2) : "memory");
}
__device__ __forceinline__ void pf4(const CUtensorMap* m, int c0, int c1) {
  asm volatile("cp.async.bulk.prefetch.tensor.4d.L2.global [%0, {%1,%2,%3,%3}];" ::"l"(m), "r"(c0), "r"(c1), "r"(0) : "memory");
}
__device__ __forceinline__ void pf_lin(const char* p, uint32_t sz) { asm volatile("cp.async.bulk.prefetch.L2.global [%0], %1;" ::"l"(p), "r"(sz) : "memory"); }
__device__ __forceinline__ void prefetch_tm(const CUtensorMap* m) { asm volatile("prefetch.tensormap [%0];" ::"l"(m) : "memory"); }
__host__ __device__ constexpr uint32_t dlo(uint32_t addr, uint32_t lbo) { return ((addr & 0x3FFFF) >> 4) | ((lbo >> 4) << 16); }
template <int I, int N, class F> __device__ __forceinline__ void sfor(F&& f) {
  if constexpr (I < N) { f(std::integral_constant<int, I>{}); sfor<I + 1, N>(f); }
}
#define WG_FENCE() asm volatile("wgmma.fence.sync.aligned;" ::: "memory")
#define WG_COMMIT() asm volatile("wgmma.commit_group.sync.aligned;" ::: "memory")
#define WG_WAIT(n) asm volatile("wgmma.wait_group.sync.aligned %0;" ::"n"(n) : "memory")
template <int N> __device__ __forceinline__ void pin(float (&a)[N]) {
#pragma unroll
  for (int i = 0; i < N; i++) asm volatile("" : "+f"(a[i])::"memory");
}
template <int N> __device__ __forceinline__ void pin(uint32_t (&a)[N]) {
#pragma unroll
  for (int i = 0; i < N; i++) asm volatile("" : "+r"(a[i])::"memory");
}
__device__ __forceinline__ uint32_t pk(float lo, float hi) { uint32_t r; asm("cvt.rn.bf16x2.f32 %0, %1, %2;" : "=r"(r) : "f"(hi), "f"(lo)); return r; }
__device__ __forceinline__ float blo(uint32_t v) { return __uint_as_float(v << 16); }
__device__ __forceinline__ float bhi(uint32_t v) { return __uint_as_float(v & 0xffff0000u); }
__device__ __forceinline__ float ex2(float x) { float y; asm("ex2.approx.ftz.f32 %0, %1;" : "=f"(y) : "f"(x)); return y; }
__device__ __forceinline__ float rcp(float x) { float y; asm("rcp.approx.ftz.f32 %0, %1;" : "=f"(y) : "f"(x)); return y; }
__device__ __forceinline__ uint4 lds128(uint32_t a) { uint4 v; asm volatile("ld.shared.v4.u32 {%0,%1,%2,%3}, [%4];" : "=r"(v.x), "=r"(v.y), "=r"(v.z), "=r"(v.w) : "r"(a + own()) : "memory"); return v; }
__device__ __forceinline__ uint32_t lds32(uint32_t a) { uint32_t v; asm volatile("ld.shared.u32 %0, [%1];" : "=r"(v) : "r"(a + own()) : "memory"); return v; }
__device__ __forceinline__ float lds_bf(uint32_t a) { uint32_t v; asm volatile("ld.shared.u16 %0, [%1];" : "=r"(v) : "r"(a + own()) : "memory"); return __uint_as_float(v << 16); }
__device__ __forceinline__ void sts128(uint32_t a, uint32_t x) { asm volatile("st.shared.v4.u32 [%0], {%1,%1,%1,%1};" ::"r"(a + own()), "r"(x) : "memory"); }
__device__ __forceinline__ void sts32(uint32_t a, uint32_t v) { asm volatile("st.shared.u32 [%0], %1;" ::"r"(a + own()), "r"(v) : "memory"); }
__device__ __forceinline__ float4 ldg_l2(const float* p) {
  float4 v; asm volatile("ld.relaxed.gpu.global.v4.f32 {%0,%1,%2,%3}, [%4];" : "=f"(v.x), "=f"(v.y), "=f"(v.z), "=f"(v.w) : "l"(p) : "memory"); return v;
}
__device__ __forceinline__ void stsm4(uint32_t a, uint32_t r0, uint32_t r1, uint32_t r2, uint32_t r3) {
  asm volatile("stmatrix.sync.aligned.m8n8.x4.shared.b16 [%0], {%1,%2,%3,%4};" ::"r"(a + own()), "r"(r0), "r"(r1), "r"(r2), "r"(r3) : "memory");
}
__device__ __forceinline__ void stsm4t(uint32_t a, uint32_t r0, uint32_t r1, uint32_t r2, uint32_t r3) {
  asm volatile("stmatrix.sync.aligned.m8n8.x4.trans.shared.b16 [%0], {%1,%2,%3,%4};" ::"r"(a + own()), "r"(r0), "r"(r1), "r"(r2), "r"(r3) : "memory");
}
__device__ __forceinline__ uint32_t hmul2(uint32_t a, uint32_t b) { uint32_t d; asm("mul.rn.bf16x2 %0, %1, %2;" : "=r"(d) : "r"(a), "r"(b)); return d; }
__device__ __forceinline__ float dot8(uint4 x, uint4 w, float acc) {
  const uint32_t p[4] = {hmul2(x.x, w.x), hmul2(x.y, w.y), hmul2(x.z, w.z), hmul2(x.w, w.w)};
#pragma unroll
  for (int i = 0; i < 4; i++) acc += blo(p[i]) + bhi(p[i]);
  return acc;
}

constexpr float LOG2E = 1.4426950408889634f;
template <int T0, int T1>
__device__ __forceinline__ void row_max(const float (&c)[4][8], float (&mx)[4][4]) {
#pragma unroll
  for (int i = 2 * T0; i < 2 * T1; i++) {
    const int t = i >> 1, r = i & 1;
    mx[t][r] = fmaxf(fmaxf(c[t][2 * r], c[t][2 * r + 1]), fmaxf(c[t][4 + 2 * r], c[t][5 + 2 * r]));
    mx[t][2 + r] = fminf(fminf(c[t][2 * r], c[t][2 * r + 1]), fminf(c[t][4 + 2 * r], c[t][5 + 2 * r]));
  }
#pragma unroll
  for (int m = 1; m <= 2; m++)
#pragma unroll
    for (int i = 4 * T0; i < 4 * T1; i++) {
      const float o = __shfl_xor_sync(0xffffffffu, mx[i >> 2][i & 3], m);
      mx[i >> 2][i & 3] = (i & 2) ? fminf(mx[i >> 2][i & 3], o) : fmaxf(mx[i >> 2][i & 3], o);
    }
#pragma unroll
  for (int i = 4 * T0; i < 4 * T1; i++) mx[i >> 2][i & 3] *= (i & 2) ? LOG2E : -LOG2E;
}
__device__ __forceinline__ void row_exp(const float (&c)[8], const float (&mx)[4], float (&e)[16]) {
#pragma unroll
  for (int i = 0; i < 8; i++) { e[i] = ex2(fmaf(c[i], LOG2E, mx[(i >> 1) & 1])); e[8 + i] = ex2(fmaf(c[i], -LOG2E, mx[2 + ((i >> 1) & 1)])); }
}

template <int G0, int U0, int OFF, int CNT, int N, int M>
__device__ __forceinline__ void gu_pack(const float (&a)[N], uint32_t (&h)[M], float sa, float sb) {
  const uint32_t s[2] = {pk(sa, sa), pk(sb, sb)};
#pragma unroll
  for (int i = 0; i < CNT; i++) h[OFF + i] = hmul2(pk(a[G0 + 2 * i] * a[U0 + 2 * i], a[G0 + 2 * i + 1] * a[U0 + 2 * i + 1]), s[i & 1]);
#pragma unroll
  for (int i = 0; i < CNT; i++) asm volatile("" : "+r"(h[OFF + i])::"memory");
}

#define REL(bar) do { if (lane == 0) mbar_arrive(bar); } while (0)

template <int W, int KA, int KB, int MODE = 0>
__device__ __forceinline__ void hg256(float (&acc)[128], uint32_t xd, uint32_t rd) {
  sfor<KA, KB>([&](auto kc) {
    constexpr int k = kc.value;
    constexpr uint32_t AI = dlo(XB + k * 32, 16), BI = dlo(RB + (k * 1024 << W), 4096 << W), BH = W ? 0x40000040 : 0x80000020;
    if constexpr (k == 0 && MODE == 1) wg_ss256_t01_z<AI, BI, BH>(acc, xd, rd); else wg_ss256_t01_a<AI, BI, BH>(acc, xd, rd);
  });
}
template <int KA, int KB, bool Z>
__device__ __forceinline__ void hg64(float (&acc)[32], const uint32_t (&a)[72], uint32_t eb) {
  sfor<KA, KB>([&](auto kc) {
    constexpr int k = kc.value;
    constexpr uint32_t BI = dlo(SB + k * 2048, 8192);
    if constexpr (Z && k == KA) wg_rs64_z<BI>(acc, a[4 * k], a[4 * k + 1], a[4 * k + 2], a[4 * k + 3], eb);
    else wg_rs64_a<BI>(acc, a[4 * k], a[4 * k + 1], a[4 * k + 2], a[4 * k + 3], eb);
  });
}
__device__ __forceinline__ void put_tile(float (&c)[32], uint32_t stg, int lane) {
  pin(c);
  if (lane == 0) asm volatile("cp.async.bulk.wait_group.read 1;" ::: "memory");
  __syncwarp();
  const int t = lane >> 3, r = lane & 7;
  const uint32_t rowa = stg + ((t & 1) * 8 + r) * 128;
#pragma unroll
  for (int q = 0; q < 4; q++)
    stsm4(rowa + (((2 * q + (t >> 1)) ^ r) << 4), pk(c[8 * q], c[8 * q + 1]), pk(c[8 * q + 2], c[8 * q + 3]), pk(c[8 * q + 4], c[8 * q + 5]), pk(c[8 * q + 6], c[8 * q + 7]));
}
__device__ __forceinline__ void send_tile(float (&c)[32], uint32_t dst, uint32_t bar) {
  pin(c);
#pragma unroll
  for (int q = 0; q < 4; q++)
    asm volatile("st.async.weak.shared::cluster.mbarrier::complete_tx::bytes.v4.b32 [%0], {%1,%2,%3,%4}, [%5];" ::"r"(dst + q * 4096),
                 "r"(pk(c[8 * q], c[8 * q + 1])), "r"(pk(c[8 * q + 2], c[8 * q + 3])), "r"(pk(c[8 * q + 4], c[8 * q + 5])), "r"(pk(c[8 * q + 6], c[8 * q + 7])), "r"(bar) : "memory");
}
__device__ __forceinline__ void recv_tile(uint4 (&v)[4], uint32_t src, uint32_t bar) {
  mbar_wait(bar);
#pragma unroll
  for (int q = 0; q < 4; q++) v[q] = lds128(src + q * 4096);
}
__device__ __forceinline__ uint32_t hadd2(uint32_t a, uint32_t b) { uint32_t d; asm("add.rn.bf16x2 %0, %1, %2;" : "=r"(d) : "r"(a), "r"(b)); return d; }
__device__ __forceinline__ void put_tile(float (&c)[32], const uint4 (&v)[4], uint32_t stg, int lane) {
  pin(c);
  if (lane == 0) asm volatile("cp.async.bulk.wait_group.read 0;" ::: "memory");
  __syncwarp();
  const int t = lane >> 3, r = lane & 7;
  const uint32_t rowa = stg + ((t & 1) * 8 + r) * 128;
#pragma unroll
  for (int q = 0; q < 4; q++)
    stsm4(rowa + (((2 * q + (t >> 1)) ^ r) << 4), hadd2(pk(c[8 * q], c[8 * q + 1]), v[q].x), hadd2(pk(c[8 * q + 2], c[8 * q + 3]), v[q].y),
          hadd2(pk(c[8 * q + 4], c[8 * q + 5]), v[q].z), hadd2(pk(c[8 * q + 6], c[8 * q + 7]), v[q].w));
}
__device__ __forceinline__ void out_tile(uint32_t stg, const CUtensorMap* tm, int col, int row, int lane) {
  asm volatile("fence.proxy.async.shared::cta;" ::: "memory");
  __syncwarp();
  if (lane == 0) {
    asm volatile("cp.reduce.async.bulk.tensor.2d.global.shared::cta.add.tile.bulk_group [%0, {%2,%3}], [%1];" ::"l"(tm), "r"(stg + own()), "r"(col), "r"(row) : "memory");
    asm volatile("cp.async.bulk.commit_group;" ::: "memory");
  }
}

#define NEXT() do { sb += 8; rd = rd == 4096 ? 0 : rd + 2048; } while (0)
#define SPLIT() mbar_wait(B_XF)
#define HEAD(...) do { mbar_wait(B_F + sb); WG_FENCE(); __VA_ARGS__; WG_COMMIT(); WG_WAIT(1); REL(B_E - 8 + sb); TS(wg, 2 + (sb >> 3)); } while (0)
#define STAGE256(W) do { NEXT(); xd += 1024; HEAD((hg256<W, 0, 1>(acc, xd, rd))); hg256<W, 1, 4>(acc, xd, rd); WG_COMMIT(); } while (0)
#define EB (((ETBL >> (sb & 24)) & 255) * 256)
#define P2STEP(CUR, PREV, ST) do { sb += 8; HEAD((hg64<0, K1, true>(CUR, a, EB))); put_tile(PREV, ST, lane); \
    WG_FENCE(); hg64<K1, K2, false>(CUR, a, EB); out_tile(ST, &P.t[M_OUT], col, row0, lane); \
    WG_FENCE(); hg64<K2, 18, false>(CUR, a, EB); WG_COMMIT(); col = (col + 64) & 511; } while (0)
#define P2SEND() do { sb += 8; HEAD((hg64<0, S1, true>(pb, a, EB))); mbar_wait(B_PR); send_tile(pa, rx + rb, bx + rb); \
    WG_FENCE(); hg64<S1, 18, false>(pb, a, EB); WG_COMMIT(); } while (0)
#define P2OUT() do { sb += 8; HEAD((hg64<0, 3, true>(pa, a, EB))); hg64<3, R1, false>(pa, a, EB); recv_tile(v, rx, bx); mbar_wait(B_ZK); mbar_wait(B_E + 8 * 19); \
    WG_FENCE(); hg64<R1, R2, false>(pa, a, EB); put_tile(pb, v, stg, lane); WG_FENCE(); hg64<R2, R3, false>(pa, a, EB); \
    out_tile(stg, &P.t[M_OUT], col, row0, lane); WG_FENCE(); hg64<R3, 18, false>(pa, a, EB); WG_COMMIT(); } while (0)

template <bool CL>
__global__ void __launch_bounds__(NTHREADS, 1)
fused_kernel(const __grid_constant__ Params P, const __nv_bfloat16* __restrict__ gate_w, __nv_bfloat16* out) {
  TS(threadIdx.x >> 7, 0);
  const bool first = threadIdx.x == 192;
  if (first) { prefetch_tm(&P.t[M_X]); prefetch_tm(&P.t[M_KV]); }
  const int b = blockIdx.x, cl = b >> 1;
  const int u = cl < 4 ? 32 + 8 * cl : cl < 36 ? cl - 4 : cl - 3 + ((cl - 36) * 37 >> 8);
  const int m = CL ? (u & 1) * 8 + (u >> 3) : (b & 7) + (b >> 1 & 8), j = CL ? (u & 6) + (b & 1) : (b >> 5) * 2 + (b >> 3 & 1);
  if (own() & 0xFFFFFF) return;
  if (first) {
#pragma unroll 1
    for (int s = 0; s < NF; s++) {
      mbar_init(B_XF + 8 * s, 1);
      asm volatile("fence.mbarrier_init.release.cluster;" ::: "memory");
      mbar_expect(B_XF + 8 * s, 32768);
      tma2(XB + s * 16384, &P.t[M_X], B_XF + 8 * s, s * 64, m * 128);
      tma3(RB + (s < 2 ? 65536 : -32768) + s * 16384, &P.t[M_KV], B_XF + 8 * s, j * 64, s * 64, 1);
    }
    TS2(4);
  }
  const int warp = __shfl_sync(0xffffffffu, threadIdx.x >> 5, 0), lane = threadIdx.x & 31;
  constexpr int rot = 0;
  if (lane == 0) {
    const int grp = warp >= 8 ? warp - 8 : warp + 4;
    if (grp < 10) {
#pragma unroll
      for (int i = 0; i < 8; i++) if (i >= NF || grp) mbar_init(BAR + grp * 64 + 8 * i, grp < 5 || grp == 9 ? 1 : grp == 5 && i == 0 ? 16 : 8);
    }
    if (CL && grp == 9) {
#pragma unroll
      for (int i = 0; i < 8; i++) mbar_expect(B_RX + 8 * i, 8192);
    }
    if (CL && (grp == 5 || grp == 9)) asm volatile("fence.mbarrier_init.release.cluster;" ::: "memory");
  }
  __syncthreads();
  if (CL) asm volatile("barrier.cluster.arrive.relaxed.aligned;" ::: "memory");
  if (warp >= 8) {
    asm volatile("setmaxnreg.dec.sync.aligned.u32 24;");
    if (warp == 8) {
      if (lane == 0) {
        asm volatile("fence.proxy.async.shared::cta;" ::: "memory");
        uint32_t dst = RB - 32768 + NF * 16384;
#pragma unroll 1
        for (int s = NF; s < 8; s++) {
          const int k0 = (rot + s * 64) & 511;
          if (s == DL) mbar_wait(B_XF);
          mbar_expect(B_XF + 8 * s, s == 7 ? 34816 : 32768);
          if (s == 7) tma2(WP, &P.t[M_WP], B_XF + 56, 0, j * 64);
          tma2(XB + s * 16384, &P.t[M_X], B_XF + 8 * s, k0, m * 128);
          if (s == PFS && m >= 14) { pf3(&P.t[M_Q], 0, (m - 14) * 64, j * 2); pf4(&P.t[M_GU1], j * 224, (m - 14) * 64); }
          if (s == 6) mbar_wait(B_E);
          tma3(dst, &P.t[M_KV], B_XF + 8 * s, j * 64, k0, 1);
          dst = dst == RB + 81920 ? RB : dst + 16384;
        }
#pragma unroll 1
        for (int s = 4; s < 20; s++) {
          mbar_wait(B_E + 8 * (s - 3));
          const uint32_t bar = B_F + 8 * s;
          mbar_expect(bar, s < 16 ? 32768 : 49152);
          const int k0 = (rot + (s < 12 ? s - 4 : s) * 64) & 511;
          if (s < 12) {
            tma4(dst + 8192, &P.t[M_GU1], bar, j * 224, k0);
            tma3(dst, &P.t[M_Q], bar, 0, k0, j * 2);
          } else {
            tma4(dst, &P.t[M_GU2], bar, j * 224 + 96, k0);
            if (s >= 16) tma2(XB + (s - 16) * 16384, &P.t[M_X], bar, k0, m * 128);
          }
          dst = dst == RB + 65536 ? RB : dst + 32768;
          if (s == m + 4) {
            if (s < 10) pf3(&P.t[M_Q], 0, (k0 + 128) & 511, j * 2);
            if (s < 18) pf4(&P.t[s < 10 ? M_GU1 : M_GU2], j * 224 + (s < 10 ? 0 : 96), (rot + (s < 10 ? s - 2 : s + 2) * 64) & 511);
          }
          if (s == (m & 7) + 8) { pf_lin(P.pf[0] + blockIdx.x * 14336, 14336); pf_lin(P.pf[1] + blockIdx.x * 4096, 4096); }
        }
        mbar_wait(B_KI);
#pragma unroll 1
        for (int i = 0; i < 8; i++) {
          mbar_wait(B_E + 8 * (i == 1 ? 18 : 16 + i));
          const uint32_t d = SB + ((ETBL >> (8 * (i & 3))) & 255) * 4096, bar = B_F + 8 * (20 + i);
          const int c0 = ((CL ? ((j ^ i ^ 1) & 1) + (j & 6) + (i & 6) : j + i) & 7) * 64;
          mbar_expect(bar, 36864);
          tma2(d + 8192, &P.t[M_WD], bar, c0, j * 224);
          tma2(d, &P.t[M_WO], bar, c0, j * 64);
        }
      }
    } else if (warp == 9) {
      unsigned ep;
      asm volatile("ld.relaxed.gpu.global.u32 %0, [%1];" : "=r"(ep) : "l"(&g_zcnt[m * 32]) : "memory");
      if (lane < M_N) prefetch_tm(&P.t[lane]);
      uint4* o = reinterpret_cast<uint4*>(out + (m * 128 + j * 16) * 512) + lane;
      ep >>= 3;
      if (lane == 0) { sts32(EPS, ep); mbar_arrive(B_EP); }
#pragma unroll 1
      for (int i = 0; i < 8; i++) {
        mbar_wait(B_E + 8 * (ZD + i * ZS / 8));
#pragma unroll
        for (int q = 0; q < 4; q++) o[(i * 4 + q) * 32] = make_uint4(0, 0, 0, 0);
      }
      uint4* z = reinterpret_cast<uint4*>(g_kv[(ep + 1) & 1][j]) + m * 34;
      z[lane] = make_uint4(0, 0, 0, 0);
      if (lane < 2) z[32 + lane] = make_uint4(0, 0, 0, 0);
      TS2(2);
      asm volatile("fence.proxy.async.global;" ::: "memory");
      __syncwarp();
      if (lane == 0) {
        asm volatile("red.release.gpu.global.add.u32 [%0], 1;" ::"l"(&g_zcnt[m * 32]) : "memory");
        TS2(3);
        mbar_wait(B_KD);
        TS2(5);
        asm volatile("red.release.gpu.global.add.u32 [%0], 1;" ::"l"(&g_kvcnt[j * 32]) : "memory");
        TS2(6);
        flag_wait(&g_kvcnt[j * 32], (ep + 1) * 16);
        TS2(7);
        asm volatile("fence.proxy.async.global;" ::: "memory");
        mbar_wait(B_E + 96);
        mbar_expect(B_KV, 8704);
        asm volatile("cp.async.bulk.shared::cluster.global.mbarrier::complete_tx::bytes [%0], [%1], 8704, [%2];" ::"r"(KF + own()), "l"(g_kv[ep & 1][j]), "r"(B_KV + own()) : "memory");
        flag_wait(&g_zcnt[m * 32], (ep + 1) * 8);
        asm volatile("fence.proxy.async.global;" ::: "memory");
        mbar_arrive(B_ZK);
      }
    } else {
      sts32(GW + (warp & 1) * 128 + lane * 4, __ldg(reinterpret_cast<const uint32_t*>(gate_w) + j * 32 + lane));
      __syncwarp();
      const int row = (warp & 1) * 64 + lane;
      const uint32_t xa = XB + (j & ~ROTM) * 16384 + row * 128 + ((lane & 7) << 4);
      float g[4] = {0.f, 0.f, 0.f, 0.f};
      mbar_wait(B_XF + 8 * (j & ~ROTM));
      TS2(10);
#pragma unroll 1
      for (int c = 0; c < 8; c++) {
        const uint4 w = lds128(GW + (warp & 1) * 128 + c * 16);
        g[0] = dot8(lds128(xa ^ (c << 4)), w, g[0]);
        g[1] = dot8(lds128((xa ^ (c << 4)) + 4096), w, g[1]);
      }
      g_gate[m][j][row] = g[0]; g_gate[m][j][row + 32] = g[1];
      __syncwarp();
      if (lane < 4) mbar_arrive(B_GX);
      TS2(11);
      if (lane == 0) {
        unsigned ep;
        asm volatile("atom.release.gpu.global.add.u32 %0, [%1], 1;" : "=r"(ep) : "l"(&g_zcnt[m * 32 + 8]) : "memory");
        TS2(12);
        if (warp == 10) flag_wait(&g_zcnt[m * 32 + 8], (ep & ~15u) + 16);
      }
      if (warp == 10) {
        __syncwarp();
        TS2(13);
        g[0] = 0.f; g[1] = 0.f;
#pragma unroll 2
        for (int i = 0; i < 8; i++) {
          const float4 v = ldg_l2(&g_gate[m][i][lane * 4]);
          g[0] += v.x; g[1] += v.y; g[2] += v.z; g[3] += v.w;
        }
#pragma unroll
        for (int q = 0; q < 2; q++) {
          const uint32_t l = pk(g[2 * q], g[2 * q + 1]);
          sts32(GV + lane * 8 + q * 4, pk(rcp(1.f + ex2(-LOG2E * blo(l))), rcp(1.f + ex2(-LOG2E * bhi(l)))));
        }
        __syncwarp();
        REL(B_G);
        TS2(15);
      }
      mbar_wait(B_KV);
#pragma unroll 1
      for (int h = (warp & 1) * 2; h < (warp & 1) * 2 + 2; h++) {
        uint4 v[4];
#pragma unroll
        for (int i = 0; i < 4; i++) v[i] = lds128(KF + h * 2048 + i * 512 + lane * 16);
        const uint32_t z = lds32(KF + 8192 + h * 128 + lane * 4), d = KI + h * 1536;
#pragma unroll
        for (int i = 0; i < 4; i++) {
          sts32(d + lane * 4 + (i >> 1) * 768 + (i & 1) * 256, pk(__uint_as_float(v[i].x), __uint_as_float(v[i].y)));
          sts32(d + lane * 4 + (i >> 1) * 768 + (i & 1) * 256 + 128, pk(__uint_as_float(v[i].z), __uint_as_float(v[i].w)));
        }
        sts128(d + (lane >> 4) * 768 + 512 + (lane & 15) * 16, pk(__uint_as_float(z), 1.f));
      }
      asm volatile("fence.proxy.async.shared::cta;" ::: "memory");
      __syncwarp();
      if (lane < 4) mbar_arrive(B_KI);
      TS2(8);
    }
  } else {
    asm volatile("setmaxnreg.inc.sync.aligned.u32 240;");
    const int wg = warp >> 2;
    const uint32_t xa = wg * 512;
    if (CL) asm volatile("barrier.cluster.wait.acquire.aligned;" ::: "memory");
    TS(wg, 1);
    uint32_t sb = 0, rd = 4096, xd = xa;
    uint32_t a[72];
    float acc[128];
    uint32_t vp[16];
#define PHI_MMA() sfor<0, 4>([&](auto tc) { constexpr int t = tc.value; wg_rs16_z<dlo(WP + t * 512, 256)>(c[t], a[4 * t], a[4 * t + 1], a[4 * t + 2], a[4 * t + 3], 0); })
#define PHI_WAIT() do { WG_WAIT(1); SPLIT(); _Pragma("unroll") for (int t = 0; t < 4; t++) pin(c[t]); } while (0)
#define BF(t, i) __float_as_uint(c[t][i])
#define BAR_WG() asm volatile("bar.sync %0, 128;" ::"r"(1 + wg) : "memory")
#define BAR_ALL() asm volatile("bar.sync 7, 256;" ::: "memory")
    {
      float ak[64];
#pragma unroll 1
      for (int s = 0; s < 8; s++) {
        mbar_wait(B_XF + sb); WG_FENCE();
        wg_ss128_t01_p<dlo(XB, 16), dlo(RB, 8192)>(ak, xd, rd, sb);
        WG_COMMIT(); WG_WAIT(1);
        if (lane == 0 && !(s & 1)) mbar_arrive(B_E - 8 + (sb >> 1));
        TS(wg, 2 + (s >> 1));
        sfor<1, 4>([&](auto kc) {
          constexpr int k = kc.value;
          wg_ss128_t01_a<dlo(XB + k * 32, 16), dlo(RB + k * 2048, 8192)>(ak, xd, rd);
        });
        WG_COMMIT();
        sb += 8; rd = rd == 5120 ? 0 : rd + 1024; xd += 1024;
      }
      sb = 32; rd = 0; xd = xa;
      HEAD((hg256<0, 0, 1, 1>(acc, xd, rd)));
      hg256<0, 1, 4>(acc, xd, rd); WG_COMMIT();
      mbar_wait(j == 0 ? B_GX : B_XF);
      pin(ak);
#pragma unroll
      for (int i = 0; i < 16; i++) { a[i] = pk(ak[2 * i], ak[2 * i + 1]); vp[i] = pk(ak[32 + 2 * i], ak[33 + 2 * i]); }
    }
    float c[4][8], mx[4][4];
    {
      const uint32_t xr = XB + (warp * 16 + (lane & 15)) * 128 + (((lane >> 4) ^ (lane & 7)) << 4);
#define PUT_V(h) do { BAR_WG(); stsm4(xr + h * 16384, vp[8 * h], vp[8 * h + 1], vp[8 * h + 2], vp[8 * h + 3]); \
      stsm4((xr ^ 32) + h * 16384, vp[8 * h + 4], vp[8 * h + 5], vp[8 * h + 6], vp[8 * h + 7]); \
      stsm4((xr ^ 64) + h * 16384, 0x3f803f80u, 0x3f803f80u, 0x3f803f80u, 0x3f803f80u); } while (0)
      const uint32_t xt = XB + 32768 + wg * 8192 + ((lane >> 4) * 8 + (lane & 7)) * 128 + ((((warp & 3) * 2 + ((lane >> 3) & 1)) ^ (lane & 7)) << 4);
#define PUT_PHI(t) do { stsm4t(xt + (t & 1) * 4096 + (t >> 1) * 16384, BF(t, 0), BF(t, 1), BF(t, 2), BF(t, 3)); \
      stsm4t(xt + (t & 1) * 4096 + 2048 + (t >> 1) * 16384, BF(t, 4), BF(t, 5), BF(t, 6), BF(t, 7)); } while (0)
      NEXT(); xd += 1024;
      HEAD({ PHI_MMA(); hg256<0, 0, 1>(acc, xd, rd); });
      hg256<0, 1, 4>(acc, xd, rd); WG_COMMIT();
      PUT_V(0);
      PHI_WAIT();
      row_max<0, 3>(c, mx);
#pragma unroll
      for (int t = 0; t < 4; t++) {
        float e[16], s[4];
        STAGE256(0); mbar_wait(j == t + 1 ? B_GX : B_XF);
        if (t == 0) { PUT_V(1); row_max<3, 4>(c, mx); }
        if (t == 1) { BAR_WG(); PUT_PHI(0); }
        if (t == 2) BAR_WG();
        row_exp(c[t], mx[t], e);
#pragma unroll
        for (int q = 0; q < 4; q++) {
          const int b = (q >> 1) * 8 + (q & 1) * 2;
          s[q] = (e[b] + e[b + 1]) + (e[b + 4] + e[b + 5]);
          s[q] += __shfl_xor_sync(0xffffffffu, s[q], 1);
        }
#pragma unroll
        for (int q = 0; q < 4; q++) s[q] = rcp(s[q] + __shfl_xor_sync(0xffffffffu, s[q], 2));
#pragma unroll
        for (int i = 0; i < 8; i++) {
          const float sc = s[(i >> 2) * 2 + (i & 1)];
          c[t][i] = __uint_as_float(pk(e[2 * i] * sc, e[2 * i + 1] * sc));
        }
        if (t) PUT_PHI(t);
      }
      asm volatile("fence.proxy.async.shared::cta;" ::: "memory");
      float kv[20], kw[NA][20];
      NEXT(); xd += 1024;
      HEAD((hg256<0, 0, 2>(acc, xd, rd)));
      BAR_ALL();
      WG_FENCE();
      sfor<0, 8>([&](auto kc) {
        constexpr int k = kc.value;
        constexpr uint32_t AI = dlo(XB + 32768 + (k >> 2) * 8192 + (k & 3) * 32, 16), BI = dlo(XB + k * 2048, 16);
        if constexpr (k < NA) wg_ss40_t01_z<AI, BI>(kw[k], 2 * xa, 2 * xa); else wg_ss40_t01_a<AI, BI>(kw[k % NA], 2 * xa, 2 * xa);
      });
      hg256<0, 2, 4>(acc, xd, rd); WG_COMMIT();
      STAGE256(0);
      mbar_wait(B_EP);
#pragma unroll
      for (int q = 0; q < NA; q++) pin(kw[q]);
#pragma unroll
      for (int i = 0; i < 20; i++) kv[i] = NA == 2 ? kw[0][i] + kw[NA - 1][i] : kw[0][i];
      float* dst = g_kv[lds32(EPS) & 1][j];
      const bool up = warp & 2;
#pragma unroll
      for (int i = 0; i < 2; i++)
        asm volatile("red.global.add.v4.f32 [%0], {%1,%2,%3,%4};" ::"l"(dst + warp * 256 + i * 128 + lane * 4),
                     "f"(up ? kv[8 + 4 * i] : kv[4 * i]), "f"(up ? kv[9 + 4 * i] : kv[4 * i + 1]), "f"(up ? kv[10 + 4 * i] : kv[4 * i + 2]), "f"(up ? kv[11 + 4 * i] : kv[4 * i + 3]) : "memory");
      if (!(lane & 2)) asm volatile("red.global.add.f32 [%0], %1;" ::"l"(dst + 2048 + warp * 16 + (lane & 1) * 8 + (lane >> 2)), "f"((lane & 1) ? kv[18] : kv[16]) : "memory");
      __syncwarp();
      REL(B_KD);
    }
    WG_WAIT(0);
    REL(B_E + sb);
    pin(acc);
#pragma unroll
    for (int i = 0; i < 16; i++) a[i] = pk(acc[2 * i], acc[2 * i + 1]);
    uint32_t h0[24];
#pragma unroll
    for (int i = 0; i < 24; i++) h0[i] = pk(acc[32 + 2 * i] * acc[80 + 2 * i], acc[33 + 2 * i] * acc[81 + 2 * i]);
    pin(h0);
    NEXT(); xd = xa + 4096;
    mbar_wait(B_F + sb); WG_FENCE();
    PHI_MMA(); WG_COMMIT();
    TS(wg, 14);
    hg256<1, 0, 4, 1>(acc, xd, rd); WG_COMMIT();
    PHI_WAIT();
    row_max<0, 2>(c, mx);
#pragma unroll
    for (int t = 0; t < 4; t++) {
      float e[16];
      if (t == 3) xd -= 8192;
      STAGE256(1); SPLIT();
      if (t == 0) row_max<2, 4>(c, mx);
      row_exp(c[t], mx[t], e);
#pragma unroll
      for (int i = 0; i < 8; i++) c[t][i] = __uint_as_float(pk(e[2 * i], e[2 * i + 1]));
      pin(c[t]);
    }
    mbar_wait(B_G);
    const float ga = lds_bf(GV + warp * 32 + (lane >> 2) * 2), gb = lds_bf(GV + warp * 32 + 16 + (lane >> 2) * 2);
    mbar_wait(B_KI);
    TS(wg, 34);
    sfor<0, 4>([&](auto tc) {
      constexpr int t = tc.value;
      float p[12], q[12];
#define O_MMA() do { wg_rs24_z<dlo(KI + t * 1536, 128)>(p, BF(t, 0), BF(t, 1), BF(t, 2), BF(t, 3), 0); \
                     wg_rs24_z<dlo(KI + t * 1536 + 768, 128)>(q, BF(t, 4), BF(t, 5), BF(t, 6), BF(t, 7), 0); } while (0)
      if constexpr (t & 1) {
        WG_FENCE(); O_MMA(); WG_COMMIT();
        hg256<1, 2, 4>(acc, xd, rd);
      } else {
        NEXT(); xd += 1024;
        HEAD({ O_MMA(); hg256<1, 0, 1>(acc, xd, rd); });
        hg256<1, 1, 2>(acc, xd, rd);
      }
      WG_COMMIT(); WG_WAIT(1); SPLIT();
      pin(p); pin(q);
      const float ra = ga * rcp(fmaf(fmaf(1e-6f, p[9], p[8]), q[9], q[8] * p[9]));
      const float rb = gb * rcp(fmaf(fmaf(1e-6f, p[11], p[10]), q[11], q[10] * p[11]));
      const float pa_ = ra * q[9], na_ = ra * p[9], pb_ = rb * q[11], nb_ = rb * p[11];
#pragma unroll
      for (int i = 0; i < 4; i++) {
        const float sp = (i & 1) ? pb_ : pa_, sn = (i & 1) ? nb_ : na_;
        a[4 * t + i] = pk(fmaf(p[2 * i], sp, q[2 * i] * sn), fmaf(p[2 * i + 1], sp, q[2 * i + 1] * sn));
      }
    });
    STAGE256(1); SPLIT();
    pin(h0);
#pragma unroll
    for (int i = 0; i < 24; i++) a[16 + i] = hmul2(h0[i], (i & 1) ? pk(1.f - gb, 1.f - gb) : pk(1.f - ga, 1.f - ga));
    float pa[32], pb[32];
    sb += 8;
    uint32_t rb = 0;
    if (CL) asm volatile("mapa.shared::cluster.u32 %0, %1, %2;" : "=r"(rb) : "r"(0), "r"((j & 1) ^ 1));
    HEAD((hg64<0, PH, true>(pa, a, (ETBL & 255) * 256)));
    if (CL && lane == 0) asm volatile("mbarrier.arrive.shared::cluster.b64 _, [%0];" ::"r"(B_PR + rb) : "memory");
    sfor<0, 8>([&](auto ic) {
      constexpr int i = ic.value;
#pragma unroll
      for (int q = 0; q < 8; q++) asm volatile("" : "+f"(acc[8 * i + q]), "+f"(acc[64 + 8 * i + q])::"memory");
      gu_pack<8 * i, 64 + 8 * i, 40 + 4 * i, 4>(acc, a, 1.f - ga, 1.f - gb);
      WG_FENCE();
      hg64<PH + i, i == 7 ? 18 : PH + i + 1, false>(pa, a, (ETBL & 255) * 256);
    });
    WG_COMMIT();
    const uint32_t stg = STG + warp * 2048;
    const int row0 = m * 128 + warp * 16;
    int col = j * 64;
    if constexpr (CL) {
      uint32_t rx = RX + threadIdx.x * 16, bx = B_RX + wg * 8;
      uint4 v[4];
#pragma unroll 1
      for (int it = 0; it < 3; it++) {
        P2SEND();
        P2OUT();
        col = (col + 128) & 511; rx += it & 1 ? -53248 : 53248; bx += 16;
      }
      P2SEND();
      recv_tile(v, rx, bx);
      WG_WAIT(0);
      TS(wg, 30);
      put_tile(pb, v, stg, lane);
      out_tile(stg, &P.t[M_OUT], col, row0, lane);
    } else {
    mbar_wait(B_ZK);
    mbar_wait(B_E + 8 * 19);
#pragma unroll 1
    for (int it = 0; it < 3; it++) {
      P2STEP(pb, pa, stg);
      P2STEP(pa, pb, stg + 16384);
    }
    P2STEP(pb, pa, stg);
    WG_WAIT(0);
    TS(wg, 30);
    put_tile(pb, stg + 16384, lane);
    out_tile(stg + 16384, &P.t[M_OUT], col, row0, lane);
    }
    if (lane == 0) asm volatile("cp.async.bulk.wait_group.read 0;" ::: "memory");
    TS(wg, 31);
  }
}

typedef CUresult (*EncFn)(CUtensorMap*, CUtensorMapDataType, cuuint32_t, void*, const cuuint64_t*, const cuuint64_t*, const cuuint32_t*, const cuuint32_t*,
                          CUtensorMapInterleave, CUtensorMapSwizzle, CUtensorMapL2promotion, CUtensorMapFloatOOBfill);

void enc(EncFn fn, CUtensorMap* t, const void* p, int rank, cuuint64_t d0, cuuint64_t d1, cuuint64_t d2, cuuint64_t s1, cuuint64_t s2, cuuint32_t b0, cuuint32_t b1, cuuint32_t b2, cuuint64_t s3 = 0) {
  const cuuint64_t gd[4] = {d0, d1, d2, 2}, gs[3] = {s1, s2, s3};
  const cuuint32_t bd[4] = {b0, b1, b2, 2}, es[4] = {1, 1, 1, 1};
  fn(t, CU_TENSOR_MAP_DATA_TYPE_BFLOAT16, rank, const_cast<void*>(p), gd, gs, bd, es, CU_TENSOR_MAP_INTERLEAVE_NONE, b0 == 16 ? CU_TENSOR_MAP_SWIZZLE_32B : b0 == 32 ? CU_TENSOR_MAP_SWIZZLE_64B : CU_TENSOR_MAP_SWIZZLE_128B,
     (CUtensorMapL2promotion)(b1 == 16 ? PO : b1 == 128 ? PX : b0 == 32 ? PA : PW), CU_TENSOR_MAP_FLOAT_OOB_FILL_NONE);
}

}

extern "C" void kernel_launch(void* const* d_in, const int* in_sizes, int n_in, void* d_out, int out_size) {
  void* fp = nullptr;
  cudaDriverEntryPointQueryResult qr;
  cudaGetDriverEntryPoint("cuTensorMapEncodeTiled", &fp, cudaEnableDefault, &qr);
  EncFn fn = (EncFn)fp;
  Params P;
  enc(fn, &P.t[M_X], d_in[0], 2, 512, 2048, 1, 1024, 0, 64, 128, 1);
  enc(fn, &P.t[M_KV], d_in[1], 3, 512, 512, 3, 3072, 1024, 64, 64, 2);
  enc(fn, &P.t[M_Q], d_in[1], 3, 32, 512, 16, 3072, 64, 32, 64, 2);
  const char *pg = (const char*)d_in[5], *pu = (const char*)d_in[6];
  const char* lo = pg < pu ? pg : pu;
  const cuuint64_t dist = pg < pu ? pu - pg : pg - pu;
  enc(fn, &P.t[M_GU1], lo, 4, 1792 - 64, 512, 3, 3584, 64, 32, 64, 3, dist);
  enc(fn, &P.t[M_GU2], lo, 4, 1792 - 64, 512, 2, 3584, 128, 64, 64, 2, dist);
  enc(fn, &P.t[M_WO], d_in[3], 2, 512, 512, 1, 1024, 0, 64, 64, 1);
  enc(fn, &P.t[M_WD], d_in[7], 2, 512, 1792, 1, 1024, 0, 64, 224, 1);
  enc(fn, &P.t[M_OUT], d_out, 2, 512, 2048, 1, 1024, 0, 64, 16, 1);
  enc(fn, &P.t[M_WP], d_in[2], 2, 16, 512, 1, 32, 0, 16, 64, 1);
  P.pf[0] = (const char*)d_in[7]; P.pf[1] = (const char*)d_in[3];
  cudaFuncSetAttribute(fused_kernel<false>, cudaFuncAttributeMaxDynamicSharedMemorySize, SMEM_BYTES);
  cudaFuncSetAttribute(fused_kernel<true>, cudaFuncAttributeMaxDynamicSharedMemorySize, SMEM_BYTES);
  cudaLaunchConfig_t cfg = {};
  cudaLaunchAttribute at;
  cfg.gridDim = dim3(128); cfg.blockDim = dim3(NTHREADS); cfg.dynamicSmemBytes = SMEM_BYTES; cfg.stream = cudaStreamPerThread;
  cfg.attrs = &at; cfg.numAttrs = 1;
  at.id = cudaLaunchAttributeClusterDimension; at.val.clusterDim.y = 1; at.val.clusterDim.z = 1;
  static int use_cl = -1;
  if (use_cl < 0) {
    int n[3] = {0, 0, 0};
    for (int i = 0; i < 3; i++) { at.val.clusterDim.x = 2 << i; cudaOccupancyMaxActiveClusters(&n[i], fused_kernel<true>, &cfg); }
    use_cl = USECL && n[0] == 66 && n[1] == 30 && n[2] == 15;
  }
  at.val.clusterDim.x = 2;
  if (use_cl) cudaLaunchKernelEx(&cfg, fused_kernel<true>, P, (const __nv_bfloat16*)d_in[8], (__nv_bfloat16*)d_out);
  else fused_kernel<false><<<128, NTHREADS, SMEM_BYTES>>>(P, (const __nv_bfloat16*)d_in[8], (__nv_bfloat16*)d_out);
}
```
